```python
import torch

def _softmax(x, axis=-1):
    return torch.softmax(x, dim=axis)
def _gelu(x):
    return torch.nn.functional.gelu(x, approximate="tanh")
def _silu(x):
    return torch.nn.functional.silu(x)
def _sigmoid(x):
    return torch.sigmoid(x)
def _layernorm(x, axis=-1, eps=1e-5):
    m = x.mean(dim=axis, keepdim=True)
    v = x.var(dim=axis, keepdim=True, unbiased=False)
    return (x - m) / torch.sqrt(v + eps)
def _scatter_add(tgt, idx, src, axis=0):
    return tgt.clone().index_add_(axis, idx, src)
def _segment_sum(src, seg, n):
    out = torch.zeros((n,) + src.shape[1:], dtype=src.dtype)
    return out.index_add_(0, seg, src)
def _pad(x, pw):
    flat = tuple(v for pair in reversed(pw) for v in pair)
    return torch.nn.functional.pad(x, flat)

kernel_name = 'concat_heads__gqa_block_cached__gqa_block_cached__near_ridge'

def setup_inputs():

    _w = (lambda a: (lambda t: t.to(torch.bfloat16) if t.is_floating_point() else t)(torch.as_tensor(a)))
    def _A_setup():
        B, Sq, D = 32, 48, 512
        Hq, Hkv, Sk, Dh = 32, 32, 48, 128
        assert Hq % Hkv == 0, (Hq, Hkv)
        return {
            "x": _w((lambda *s: torch.randn(*s, dtype=torch.bfloat16) * 0.8)(B, Sq, D)),
            "k_cache": _w((lambda *s: torch.randn(*s, dtype=torch.bfloat16) * 0.8)(B, Hkv, Sk, Dh)),
            "v_cache": _w((lambda *s: torch.randn(*s, dtype=torch.bfloat16) * 0.05)(B, Hkv, Sk, Dh)),
            "wq": _w((lambda *s: torch.randn(*s, dtype=torch.bfloat16) * 0.8)(D, Hq * Dh) * (D ** -0.5)),
            "wo": _w((lambda *s: torch.randn(*s, dtype=torch.bfloat16) * 0.05)(Hq * Dh, D) * ((Hq * Dh) ** -0.5)),
        }
    _A_in = _A_setup()

    def _B_setup():
        B, Sq, D = 32, 48, 512
        Hq, Hkv, Sk, Dh = 32, 32, 48, 128
        assert Hq % Hkv == 0, (Hq, Hkv)
        return {
            "x": _w((lambda *s: torch.randn(*s, dtype=torch.bfloat16) * 0.8)(B, Sq, D)),
            "k_cache": _w((lambda *s: torch.randn(*s, dtype=torch.bfloat16) * 0.8)(B, Hkv, Sk, Dh)),
            "v_cache": _w((lambda *s: torch.randn(*s, dtype=torch.bfloat16) * 0.05)(B, Hkv, Sk, Dh)),
            "wq": _w((lambda *s: torch.randn(*s, dtype=torch.bfloat16) * 0.8)(D, Hq * Dh) * (D ** -0.5)),
            "wo": _w((lambda *s: torch.randn(*s, dtype=torch.bfloat16) * 0.05)(Hq * Dh, D) * ((Hq * Dh) ** -0.5)),
        }
    _B_in = _B_setup()

    return {
        "A_x": _A_in["x"],
        "A_k_cache": _A_in["k_cache"],
        "A_v_cache": _A_in["v_cache"],
        "A_wq": _A_in["wq"],
        "A_wo": _A_in["wo"],
        "B_x": _B_in["x"],
        "B_k_cache": _B_in["k_cache"],
        "B_v_cache": _B_in["v_cache"],
        "B_wq": _B_in["wq"],
        "B_wo": _B_in["wo"],
    }

def reference(A_x, A_k_cache, A_v_cache, A_wq, A_wo, B_x, B_k_cache, B_v_cache, B_wq, B_wo):
    def _A_ref(x, k_cache, v_cache, wq, wo):
        B, Sq, D = x.shape
        Hq, Dh = 32, 128
        Hkv = k_cache.shape[1]
        rep = Hq // Hkv
        q = (lambda x, *d: x.permute(*d))((x @ wq).reshape(B, Sq, Hq, Dh), 0, 2, 1, 3)
        k = (lambda x, n, axis: torch.repeat_interleave(x, n, dim=axis))(k_cache, rep, axis=1)
        v = (lambda x, n, axis: torch.repeat_interleave(x, n, dim=axis))(v_cache, rep, axis=1)
        scores = torch.einsum("bhqd,bhkd->bhqk", q, k) * (Dh ** -0.5)
        p = _softmax(scores, axis=-1)
        o = torch.einsum("bhqk,bhkd->bhqd", p, v)
        return (lambda x, *d: x.permute(*d))(o, 0, 2, 1, 3).reshape(B, Sq, Hq * Dh) @ wo

    def _B_ref(x, k_cache, v_cache, wq, wo):
        B, Sq, D = x.shape
        Hq, Dh = 32, 128
        Hkv = k_cache.shape[1]
        rep = Hq // Hkv
        q = (lambda x, *d: x.permute(*d))((x @ wq).reshape(B, Sq, Hq, Dh), 0, 2, 1, 3)
        k = (lambda x, n, axis: torch.repeat_interleave(x, n, dim=axis))(k_cache, rep, axis=1)
        v = (lambda x, n, axis: torch.repeat_interleave(x, n, dim=axis))(v_cache, rep, axis=1)
        scores = torch.einsum("bhqd,bhkd->bhqk", q, k) * (Dh ** -0.5)
        p = _softmax(scores, axis=-1)
        o = torch.einsum("bhqk,bhkd->bhqd", p, v)
        return (lambda x, *d: x.permute(*d))(o, 0, 2, 1, 3).reshape(B, Sq, Hq * Dh) @ wo

    a = _A_ref(A_x, A_k_cache, A_v_cache, A_wq, A_wo)
    b = _B_ref(B_x, B_k_cache, B_v_cache, B_wq, B_wo)
    return torch.concatenate([a, b], axis=-1)
```

```cpp
#include <cuda_runtime.h>
#include <cuda_bf16.h>
#include <cuda.h>
#include <stdint.h>

#define GGROUP 4
#define GPEND 1
#define PF_DIST 0
#define PF_START 11
#define PINGPONG 1
#define PP_HAND 3
#define WO_PF 3
#define WO_PF_ON 1
#define PV7_AT 1
#define EF_WO 0
#define EF_O 1
#define DBG_NOKV 0
#define DBG_KVSAME 0
#define QDEPTH 1
namespace fk {

constexpr int NTHREADS = 512;
constexpr int NCTA = 128;

constexpr int X_SLOT   = 12288;
constexpr int X_NS     = 9;
constexpr int OFF_X    = 0;
constexpr int QO_BUF   = 24576;
constexpr int OFF_QO   = 110592;
constexpr int OFF_K    = 159744;
constexpr int OFF_V    = 184320;
constexpr int OFF_P    = 208896;
constexpr int OFF_WP   = 221184;
constexpr int P2_NST   = 5;
constexpr int OFF_BAR  = 229376;
constexpr int SMEM_BYTES = OFF_BAR + 768 + 1024 + 1024;
constexpr int NWQ = 30;

__device__ __forceinline__ constexpr uint32_t w_stage(int g, int ks) {
  return ks < 3 ? OFF_K + (ks * 2 + g) * 8192 : (ks < 6 ? OFF_QO + ((ks - 3) * 2 + g) * 8192 : (g ? 98304 : OFF_P) + (ks - 6) * 8192);
}
__device__ __forceinline__ uint32_t p2_a(int st, int g) {
  return st == 0 ? 12288 + g * 8192 : st == 1 ? 61440 + g * 8192 : st == 2 ? OFF_K + g * 8192 : st == 3 ? (g ? 102400 : 53248) : OFF_P + g * 8192;
}
__device__ __forceinline__ uint32_t p2_b(int st) {
  return st == 0 ? 28672 : st == 1 ? 77824 : st == 2 ? OFF_QO : st == 3 ? OFF_V : OFF_QO + QO_BUF;
}

constexpr int B_XFULL = 0, B_XEMPTY = 9, B_WFULL = 18, B_QFULL = 34, B_QEMPTY = 36, B_KFULL = 38, B_VFULL = 40,
              B_P2FULL = 42, B_P2EMPTY = 47, B_WDONE = 52, B_KEMPTY = 54, B_WFREE = 55, B_VEMPTY = 56, B_PFULL = 57, B_OFULL = 58,
              B_OST = 60, B_KDONE = 62, B_VDONE = 63, B_HREADY = 64;

struct __align__(64) Params {
  CUtensorMap x[2], wq[2], k[2], v[2], wo[2], o, out_st;
  const __nv_bfloat16* kp[2];
  const __nv_bfloat16* vp[2];
  const __nv_bfloat16* wop[2];
  const __nv_bfloat16* xp[2];
};

__device__ __nv_bfloat16 g_O[3072 * 4096];
__device__ uint4 g_part[NCTA * 12 * 256];
__device__ unsigned g_oflag[2 * 16 * 32];
__device__ unsigned g_done;

#define PROF(idx) do {} while (0)
__device__ __forceinline__ uint32_t smem_u32(const void* p) { return (uint32_t)__cvta_generic_to_shared(p); }
__device__ __forceinline__ void mbar_init(uint32_t bar, int cnt) { asm volatile("mbarrier.init.shared::cta.b64 [%0], %1;" :: "r"(bar), "r"(cnt) : "memory"); }
__device__ __forceinline__ void mbar_expect_tx(uint32_t bar, uint32_t bytes) { asm volatile("mbarrier.arrive.expect_tx.shared::cta.b64 _, [%0], %1;" :: "r"(bar), "r"(bytes) : "memory"); }
__device__ __forceinline__ void mbar_arrive(uint32_t bar) { asm volatile("mbarrier.arrive.shared::cta.b64 _, [%0];" :: "r"(bar) : "memory"); }
__device__ __forceinline__ void mbar_arrive_cta(uint32_t bar, uint32_t cta) {
  asm volatile("{\n.reg .b32 r;\nmapa.shared::cluster.u32 r, %0, %1;\nmbarrier.arrive.shared::cluster.b64 _, [r];\n}\n" :: "r"(bar), "r"(cta) : "memory");
}
__device__ __forceinline__ uint32_t mbar_try(uint32_t bar, uint32_t parity) {
  uint32_t ok;
  asm volatile("{\n.reg .pred p;\nmbarrier.try_wait.parity.shared::cta.b64 p, [%1], %2;\nselp.u32 %0, 1, 0, p;\n}\n" : "=r"(ok) : "r"(bar), "r"(parity) : "memory");
  return ok;
}
__device__ __forceinline__ void mbar_wait(uint32_t bar, uint32_t parity) {
  if (mbar_try(bar, parity)) return;
  uint32_t it = 0;
  while (!mbar_try(bar, parity)) { if (++it > (1u << 22)) __trap(); }
}
__device__ __forceinline__ void tma_ld(uint32_t dst, const CUtensorMap* m, int c0, int c1, uint32_t bar) {
  asm volatile("cp.async.bulk.tensor.2d.shared::cluster.global.mbarrier::complete_tx::bytes [%0], [%1, {%3, %4}], [%2];"
               :: "r"(dst), "l"(m), "r"(bar), "r"(c0), "r"(c1) : "memory");
}
__device__ __forceinline__ void tma_ld_hint(uint32_t dst, const CUtensorMap* m, int c0, int c1, uint32_t bar, uint64_t pol) {
  asm volatile("cp.async.bulk.tensor.2d.shared::cluster.global.mbarrier::complete_tx::bytes.L2::cache_hint [%0], [%1, {%3, %4}], [%2], %5;"
               :: "r"(dst), "l"(m), "r"(bar), "r"(c0), "r"(c1), "l"(pol) : "memory");
}
__device__ __forceinline__ void tma_ld_mc(uint32_t dst, const CUtensorMap* m, int c0, int c1, uint32_t bar) {
  asm volatile("cp.async.bulk.tensor.2d.shared::cluster.global.mbarrier::complete_tx::bytes.multicast::cluster [%0], [%1, {%3, %4}], [%2], %5;"
               :: "r"(dst), "l"(m), "r"(bar), "r"(c0), "r"(c1), "h"((uint16_t)3) : "memory");
}
__device__ __forceinline__ void tma_ld_mc_hint(uint32_t dst, const CUtensorMap* m, int c0, int c1, uint32_t bar, uint64_t pol) {
  asm volatile("cp.async.bulk.tensor.2d.shared::cluster.global.mbarrier::complete_tx::bytes.multicast::cluster.L2::cache_hint [%0], [%1, {%3, %4}], [%2], %5, %6;"
               :: "r"(dst), "l"(m), "r"(bar), "r"(c0), "r"(c1), "h"((uint16_t)3), "l"(pol) : "memory");
}
__device__ __forceinline__ void tma_st_hint(const CUtensorMap* m, int c0, int c1, uint32_t src, uint64_t pol) {
  asm volatile("cp.async.bulk.tensor.2d.global.shared::cta.bulk_group.L2::cache_hint [%0, {%2, %3}], [%1], %4;" :: "l"(m), "r"(src), "r"(c0), "r"(c1), "l"(pol) : "memory");
}
__device__ __forceinline__ void tma_st(const CUtensorMap* m, int c0, int c1, uint32_t src) {
  asm volatile("cp.async.bulk.tensor.2d.global.shared::cta.bulk_group [%0, {%2, %3}], [%1];" :: "l"(m), "r"(src), "r"(c0), "r"(c1) : "memory");
}
__device__ __forceinline__ void bulk_commit() { asm volatile("cp.async.bulk.commit_group;" ::: "memory"); }
template <int N> __device__ __forceinline__ void bulk_wait_read() { asm volatile("cp.async.bulk.wait_group.read %0;" :: "n"(N) : "memory"); }
template <int N> __device__ __forceinline__ void bulk_wait() { asm volatile("cp.async.bulk.wait_group %0;" :: "n"(N) : "memory"); }
__device__ __forceinline__ void l2_prefetch(const void* p, uint32_t bytes) { asm volatile("cp.async.bulk.prefetch.L2.global [%0], %1;" :: "l"(p), "r"(bytes) : "memory"); }
__device__ __forceinline__ void l2_prefetch_hint(const void* p, uint32_t bytes, uint64_t pol) { asm volatile("cp.async.bulk.prefetch.L2.global.L2::cache_hint [%0], %1, %2;" :: "l"(p), "r"(bytes), "l"(pol) : "memory"); }
__device__ __forceinline__ uint64_t policy_evict_first() { uint64_t pol; asm volatile("createpolicy.fractional.L2::evict_first.b64 %0, 1.0;" : "=l"(pol)); return pol; }
__device__ __forceinline__ void fence_async_smem() { asm volatile("fence.proxy.async.shared::cta;" ::: "memory"); }
__device__ __forceinline__ void fence_async_all() { asm volatile("fence.proxy.async;" ::: "memory"); }
__device__ __forceinline__ void wg_fence() { asm volatile("wgmma.fence.sync.aligned;" ::: "memory"); }
__device__ __forceinline__ void wg_commit() { asm volatile("wgmma.commit_group.sync.aligned;" ::: "memory"); }
template <int N> __device__ __forceinline__ void wg_wait() { asm volatile("wgmma.wait_group.sync.aligned %0;" :: "n"(N) : "memory"); }
__device__ __forceinline__ void cluster_sync() { asm volatile("barrier.cluster.arrive.relaxed.aligned;\nbarrier.cluster.wait.aligned;\n" ::: "memory"); }
__device__ __forceinline__ void named_arrive(int id, int n) { asm volatile("bar.arrive %0, %1;" :: "r"(id), "r"(n) : "memory"); }
__device__ __forceinline__ uint32_t mbar_test(uint32_t bar, uint32_t parity) {
  uint32_t ok;
  asm volatile("{\n.reg .pred p;\nmbarrier.test_wait.parity.shared::cta.b64 p, [%1], %2;\nselp.u32 %0, 1, 0, p;\n}\n" : "=r"(ok) : "r"(bar), "r"(parity) : "memory");
  return ok;
}
__device__ __forceinline__ void named_bar(int id, int n) { asm volatile("bar.sync %0, %1;" :: "r"(id), "r"(n) : "memory"); }
__device__ __forceinline__ uint32_t desc_lo(uint32_t addr, uint32_t lbo) { return ((addr & 0x3FFFF) >> 4) | ((lbo >> 4) << 16); }
__device__ __forceinline__ uint32_t opaque(uint32_t v) { asm volatile("mov.u32 %0, %0;" : "+r"(v)); return v; }
__device__ __forceinline__ uint32_t pack_bf16(float lo, float hi) {
  uint32_t r; asm("cvt.rn.bf16x2.f32 %0, %1, %2;" : "=r"(r) : "f"(hi), "f"(lo)); return r;
}
__device__ __forceinline__ void ldsm_x4_t(uint32_t (&r)[4], uint32_t addr) {
  asm volatile("ldmatrix.sync.aligned.m8n8.x4.trans.shared.b16 {%0,%1,%2,%3}, [%4];" : "=r"(r[0]), "=r"(r[1]), "=r"(r[2]), "=r"(r[3]) : "r"(addr) : "memory");
}
__device__ __forceinline__ void stsm_x4_t(uint32_t addr, uint32_t a, uint32_t b, uint32_t c, uint32_t d) {
  asm volatile("stmatrix.sync.aligned.m8n8.x4.trans.shared.b16 [%0], {%1,%2,%3,%4};" :: "r"(addr), "r"(a), "r"(b), "r"(c), "r"(d) : "memory");
}
__device__ __forceinline__ void stsm_x4(uint32_t addr, uint32_t a, uint32_t b, uint32_t c, uint32_t d) {
  asm volatile("stmatrix.sync.aligned.m8n8.x4.shared.b16 [%0], {%1,%2,%3,%4};" :: "r"(addr), "r"(a), "r"(b), "r"(c), "r"(d) : "memory");
}
__device__ __forceinline__ unsigned ld_acquire(const unsigned* p) { unsigned v; asm volatile("ld.acquire.gpu.global.u32 %0, [%1];" : "=r"(v) : "l"(p) : "memory"); return v; }
__device__ __forceinline__ unsigned ld_relaxed(const unsigned* p) { unsigned v; asm volatile("ld.relaxed.gpu.global.u32 %0, [%1];" : "=r"(v) : "l"(p) : "memory"); return v; }
__device__ __forceinline__ void st_relaxed(unsigned* p, unsigned v) { asm volatile("st.relaxed.gpu.global.u32 [%0], %1;" :: "l"(p), "r"(v) : "memory"); }
__device__ __forceinline__ void st_release(unsigned* p, unsigned v) { asm volatile("st.release.gpu.global.u32 [%0], %1;" :: "l"(p), "r"(v) : "memory"); }
__device__ __forceinline__ void flag_wait(const unsigned* p, unsigned epoch) {
  uint32_t it = 0;
  while (ld_acquire(p) != epoch) { if (++it > (1u << 24)) __trap(); }
}
__device__ __forceinline__ int fresh_ctaid() { int v; asm volatile("mov.u32 %0, %%ctaid.x;" : "=r"(v)); return v; }
__device__ __forceinline__ int fresh_tid() { int v; asm volatile("mov.u32 %0, %%tid.x;" : "=r"(v)); return v; }
__device__ __forceinline__ unsigned lds_u32(uint32_t a) { unsigned v; asm volatile("ld.shared.u32 %0, [%1];" : "=r"(v) : "r"(a) : "memory"); return v; }
__device__ __forceinline__ float ex2(float x) { float y; asm("ex2.approx.ftz.f32 %0, %1;" : "=f"(y) : "f"(x)); return y; }

__device__ __forceinline__ void wgmma_rs_n96_z(float (&d)[48], uint32_t a0, uint32_t a1, uint32_t a2, uint32_t a3, uint32_t db) {
  asm volatile("{\n.reg .pred p;\n.reg .b64 db;\nsetp.ne.b32 p, 0, 0;\nmov.b64 db, {%52, 0x40000040};\n"
    "wgmma.mma_async.sync.aligned.m64n96k16.f32.bf16.bf16 {%0, %1, %2, %3, %4, %5, %6, %7, %8, %9, %10, %11, %12, %13, %14, %15, %16, %17, %18, %19, %20, %21, %22, %23, %24, %25, %26, %27, %28, %29, %30, %31, %32, %33, %34, %35, %36, %37, %38, %39, %40, %41, %42, %43, %44, %45, %46, %47}, {%48, %49, %50, %51}, db, p, 1, 1, 0;\n}\n"
    : "=f"(d[0]), "=f"(d[1]), "=f"(d[2]), "=f"(d[3]), "=f"(d[4]), "=f"(d[5]), "=f"(d[6]), "=f"(d[7]), "=f"(d[8]), "=f"(d[9]), "=f"(d[10]), "=f"(d[11]), "=f"(d[12]), "=f"(d[13]), "=f"(d[14]), "=f"(d[15]), "=f"(d[16]), "=f"(d[17]), "=f"(d[18]), "=f"(d[19]), "=f"(d[20]), "=f"(d[21]), "=f"(d[22]), "=f"(d[23]), "=f"(d[24]), "=f"(d[25]), "=f"(d[26]), "=f"(d[27]), "=f"(d[28]), "=f"(d[29]), "=f"(d[30]), "=f"(d[31]), "=f"(d[32]), "=f"(d[33]), "=f"(d[34]), "=f"(d[35]), "=f"(d[36]), "=f"(d[37]), "=f"(d[38]), "=f"(d[39]), "=f"(d[40]), "=f"(d[41]), "=f"(d[42]), "=f"(d[43]), "=f"(d[44]), "=f"(d[45]), "=f"(d[46]), "=f"(d[47])
    : "r"(a0), "r"(a1), "r"(a2), "r"(a3), "r"(db));
}

__device__ __forceinline__ void wgmma_ss_n48_z(float (&d)[24], uint32_t da, uint32_t db) {
  asm volatile("{\n.reg .pred p;\n.reg .b64 da, db;\nsetp.ne.b32 p, 0, 0;\nmov.b64 da, {%24, 0x40000040};\nmov.b64 db, {%25, 0x40000040};\n"
    "wgmma.mma_async.sync.aligned.m64n48k16.f32.bf16.bf16 {%0, %1, %2, %3, %4, %5, %6, %7, %8, %9, %10, %11, %12, %13, %14, %15, %16, %17, %18, %19, %20, %21, %22, %23}, da, db, p, 1, 1, 0, 0;\n}\n"
    : "=f"(d[0]), "=f"(d[1]), "=f"(d[2]), "=f"(d[3]), "=f"(d[4]), "=f"(d[5]), "=f"(d[6]), "=f"(d[7]), "=f"(d[8]), "=f"(d[9]), "=f"(d[10]), "=f"(d[11]), "=f"(d[12]), "=f"(d[13]), "=f"(d[14]), "=f"(d[15]), "=f"(d[16]), "=f"(d[17]), "=f"(d[18]), "=f"(d[19]), "=f"(d[20]), "=f"(d[21]), "=f"(d[22]), "=f"(d[23])
    : "r"(da), "r"(db));
}

__device__ __forceinline__ void wgmma_ss_n48_ta_z(float (&d)[24], uint32_t da, uint32_t db) {
  asm volatile("{\n.reg .pred p;\n.reg .b64 da, db;\nsetp.ne.b32 p, 0, 0;\nmov.b64 da, {%24, 0x40000040};\nmov.b64 db, {%25, 0x40000040};\n"
    "wgmma.mma_async.sync.aligned.m64n48k16.f32.bf16.bf16 {%0, %1, %2, %3, %4, %5, %6, %7, %8, %9, %10, %11, %12, %13, %14, %15, %16, %17, %18, %19, %20, %21, %22, %23}, da, db, p, 1, 1, 1, 0;\n}\n"
    : "=f"(d[0]), "=f"(d[1]), "=f"(d[2]), "=f"(d[3]), "=f"(d[4]), "=f"(d[5]), "=f"(d[6]), "=f"(d[7]), "=f"(d[8]), "=f"(d[9]), "=f"(d[10]), "=f"(d[11]), "=f"(d[12]), "=f"(d[13]), "=f"(d[14]), "=f"(d[15]), "=f"(d[16]), "=f"(d[17]), "=f"(d[18]), "=f"(d[19]), "=f"(d[20]), "=f"(d[21]), "=f"(d[22]), "=f"(d[23])
    : "r"(da), "r"(db));
}

__device__ __forceinline__ void wgmma_rs_n96(float (&d)[48], uint32_t a0, uint32_t a1, uint32_t a2, uint32_t a3, uint32_t db, int scale_d) {
  asm volatile("{\n.reg .pred p;\n.reg .b64 db;\nsetp.ne.b32 p, %53, 0;\nmov.b64 db, {%52, 0x40000040};\n"
    "wgmma.mma_async.sync.aligned.m64n96k16.f32.bf16.bf16 {%0, %1, %2, %3, %4, %5, %6, %7, %8, %9, %10, %11, %12, %13, %14, %15, %16, %17, %18, %19, %20, %21, %22, %23, %24, %25, %26, %27, %28, %29, %30, %31, %32, %33, %34, %35, %36, %37, %38, %39, %40, %41, %42, %43, %44, %45, %46, %47}, {%48, %49, %50, %51}, db, p, 1, 1, 0;\n}\n"
    : "+f"(d[0]), "+f"(d[1]), "+f"(d[2]), "+f"(d[3]), "+f"(d[4]), "+f"(d[5]), "+f"(d[6]), "+f"(d[7]), "+f"(d[8]), "+f"(d[9]), "+f"(d[10]), "+f"(d[11]), "+f"(d[12]), "+f"(d[13]), "+f"(d[14]), "+f"(d[15]), "+f"(d[16]), "+f"(d[17]), "+f"(d[18]), "+f"(d[19]), "+f"(d[20]), "+f"(d[21]), "+f"(d[22]), "+f"(d[23]), "+f"(d[24]), "+f"(d[25]), "+f"(d[26]), "+f"(d[27]), "+f"(d[28]), "+f"(d[29]), "+f"(d[30]), "+f"(d[31]), "+f"(d[32]), "+f"(d[33]), "+f"(d[34]), "+f"(d[35]), "+f"(d[36]), "+f"(d[37]), "+f"(d[38]), "+f"(d[39]), "+f"(d[40]), "+f"(d[41]), "+f"(d[42]), "+f"(d[43]), "+f"(d[44]), "+f"(d[45]), "+f"(d[46]), "+f"(d[47])
    : "r"(a0), "r"(a1), "r"(a2), "r"(a3), "r"(db), "r"(scale_d));
}

__device__ __forceinline__ void wgmma_ss_n96_ta(float (&d)[48], uint32_t da, uint32_t db, int scale_d) {
  asm volatile("{\n.reg .pred p;\n.reg .b64 da, db;\nsetp.ne.b32 p, %50, 0;\nmov.b64 da, {%48, 0x40000040};\nmov.b64 db, {%49, 0x40000040};\n"
    "wgmma.mma_async.sync.aligned.m64n96k16.f32.bf16.bf16 {%0, %1, %2, %3, %4, %5, %6, %7, %8, %9, %10, %11, %12, %13, %14, %15, %16, %17, %18, %19, %20, %21, %22, %23, %24, %25, %26, %27, %28, %29, %30, %31, %32, %33, %34, %35, %36, %37, %38, %39, %40, %41, %42, %43, %44, %45, %46, %47}, da, db, p, 1, 1, 1, 0;\n}\n"
    : "+f"(d[0]), "+f"(d[1]), "+f"(d[2]), "+f"(d[3]), "+f"(d[4]), "+f"(d[5]), "+f"(d[6]), "+f"(d[7]), "+f"(d[8]), "+f"(d[9]), "+f"(d[10]), "+f"(d[11]), "+f"(d[12]), "+f"(d[13]), "+f"(d[14]), "+f"(d[15]), "+f"(d[16]), "+f"(d[17]), "+f"(d[18]), "+f"(d[19]), "+f"(d[20]), "+f"(d[21]), "+f"(d[22]), "+f"(d[23]), "+f"(d[24]), "+f"(d[25]), "+f"(d[26]), "+f"(d[27]), "+f"(d[28]), "+f"(d[29]), "+f"(d[30]), "+f"(d[31]), "+f"(d[32]), "+f"(d[33]), "+f"(d[34]), "+f"(d[35]), "+f"(d[36]), "+f"(d[37]), "+f"(d[38]), "+f"(d[39]), "+f"(d[40]), "+f"(d[41]), "+f"(d[42]), "+f"(d[43]), "+f"(d[44]), "+f"(d[45]), "+f"(d[46]), "+f"(d[47])
    : "r"(da), "r"(db), "r"(scale_d));
}

__device__ __forceinline__ void wgmma_ss_n48(float (&d)[24], uint32_t da, uint32_t db, int scale_d) {
  asm volatile("{\n.reg .pred p;\n.reg .b64 da, db;\nsetp.ne.b32 p, %26, 0;\nmov.b64 da, {%24, 0x40000040};\nmov.b64 db, {%25, 0x40000040};\n"
    "wgmma.mma_async.sync.aligned.m64n48k16.f32.bf16.bf16 {%0, %1, %2, %3, %4, %5, %6, %7, %8, %9, %10, %11, %12, %13, %14, %15, %16, %17, %18, %19, %20, %21, %22, %23}, da, db, p, 1, 1, 0, 0;\n}\n"
    : "+f"(d[0]), "+f"(d[1]), "+f"(d[2]), "+f"(d[3]), "+f"(d[4]), "+f"(d[5]), "+f"(d[6]), "+f"(d[7]), "+f"(d[8]), "+f"(d[9]), "+f"(d[10]), "+f"(d[11]), "+f"(d[12]), "+f"(d[13]), "+f"(d[14]), "+f"(d[15]), "+f"(d[16]), "+f"(d[17]), "+f"(d[18]), "+f"(d[19]), "+f"(d[20]), "+f"(d[21]), "+f"(d[22]), "+f"(d[23])
    : "r"(da), "r"(db), "r"(scale_d));
}

__device__ __forceinline__ void wgmma_ss_n48_ta(float (&d)[24], uint32_t da, uint32_t db, int scale_d) {
  asm volatile("{\n.reg .pred p;\n.reg .b64 da, db;\nsetp.ne.b32 p, %26, 0;\nmov.b64 da, {%24, 0x40000040};\nmov.b64 db, {%25, 0x40000040};\n"
    "wgmma.mma_async.sync.aligned.m64n48k16.f32.bf16.bf16 {%0, %1, %2, %3, %4, %5, %6, %7, %8, %9, %10, %11, %12, %13, %14, %15, %16, %17, %18, %19, %20, %21, %22, %23}, da, db, p, 1, 1, 1, 0;\n}\n"
    : "+f"(d[0]), "+f"(d[1]), "+f"(d[2]), "+f"(d[3]), "+f"(d[4]), "+f"(d[5]), "+f"(d[6]), "+f"(d[7]), "+f"(d[8]), "+f"(d[9]), "+f"(d[10]), "+f"(d[11]), "+f"(d[12]), "+f"(d[13]), "+f"(d[14]), "+f"(d[15]), "+f"(d[16]), "+f"(d[17]), "+f"(d[18]), "+f"(d[19]), "+f"(d[20]), "+f"(d[21]), "+f"(d[22]), "+f"(d[23])
    : "r"(da), "r"(db), "r"(scale_d));
}

__device__ __forceinline__ void wgmma_ss_n192_ta(float (&d)[48], float (&e)[48], uint32_t da, uint32_t db, int scale_d) {
  asm volatile("{\n.reg .pred p;\n.reg .b64 da, db;\nsetp.ne.b32 p, %98, 0;\nmov.b64 da, {%96, 0x40000040};\nmov.b64 db, {%97, 0x40000040};\n"
    "wgmma.mma_async.sync.aligned.m64n192k16.f32.bf16.bf16 {%0, %1, %2, %3, %4, %5, %6, %7, %8, %9, %10, %11, %12, %13, %14, %15, %16, %17, %18, %19, %20, %21, %22, %23, %24, %25, %26, %27, %28, %29, %30, %31, %32, %33, %34, %35, %36, %37, %38, %39, %40, %41, %42, %43, %44, %45, %46, %47, %48, %49, %50, %51, %52, %53, %54, %55, %56, %57, %58, %59, %60, %61, %62, %63, %64, %65, %66, %67, %68, %69, %70, %71, %72, %73, %74, %75, %76, %77, %78, %79, %80, %81, %82, %83, %84, %85, %86, %87, %88, %89, %90, %91, %92, %93, %94, %95}, da, db, p, 1, 1, 1, 0;\n}\n"
    : "+f"(d[0]), "+f"(d[1]), "+f"(d[2]), "+f"(d[3]), "+f"(d[4]), "+f"(d[5]), "+f"(d[6]), "+f"(d[7]), "+f"(d[8]), "+f"(d[9]), "+f"(d[10]), "+f"(d[11]), "+f"(d[12]), "+f"(d[13]), "+f"(d[14]), "+f"(d[15]), "+f"(d[16]), "+f"(d[17]), "+f"(d[18]), "+f"(d[19]), "+f"(d[20]), "+f"(d[21]), "+f"(d[22]), "+f"(d[23]), "+f"(d[24]), "+f"(d[25]), "+f"(d[26]), "+f"(d[27]), "+f"(d[28]), "+f"(d[29]), "+f"(d[30]), "+f"(d[31]), "+f"(d[32]), "+f"(d[33]), "+f"(d[34]), "+f"(d[35]), "+f"(d[36]), "+f"(d[37]), "+f"(d[38]), "+f"(d[39]), "+f"(d[40]), "+f"(d[41]), "+f"(d[42]), "+f"(d[43]), "+f"(d[44]), "+f"(d[45]), "+f"(d[46]), "+f"(d[47]), "+f"(e[0]), "+f"(e[1]), "+f"(e[2]), "+f"(e[3]), "+f"(e[4]), "+f"(e[5]), "+f"(e[6]), "+f"(e[7]), "+f"(e[8]), "+f"(e[9]), "+f"(e[10]), "+f"(e[11]), "+f"(e[12]), "+f"(e[13]), "+f"(e[14]), "+f"(e[15]), "+f"(e[16]), "+f"(e[17]), "+f"(e[18]), "+f"(e[19]), "+f"(e[20]), "+f"(e[21]), "+f"(e[22]), "+f"(e[23]), "+f"(e[24]), "+f"(e[25]), "+f"(e[26]), "+f"(e[27]), "+f"(e[28]), "+f"(e[29]), "+f"(e[30]), "+f"(e[31]), "+f"(e[32]), "+f"(e[33]), "+f"(e[34]), "+f"(e[35]), "+f"(e[36]), "+f"(e[37]), "+f"(e[38]), "+f"(e[39]), "+f"(e[40]), "+f"(e[41]), "+f"(e[42]), "+f"(e[43]), "+f"(e[44]), "+f"(e[45]), "+f"(e[46]), "+f"(e[47])
    : "r"(da), "r"(db), "r"(scale_d));
}

template <int NT = 12>
__device__ __forceinline__ void store_acc_T(const float* acc, uint32_t tile_addr_plus_fragoff) {
#pragma unroll
  for (int jj = 0; jj < NT; jj += 2) {
    stsm_x4_t(tile_addr_plus_fragoff + jj * 1024,
              pack_bf16(acc[4 * jj + 0], acc[4 * jj + 1]), pack_bf16(acc[4 * jj + 2], acc[4 * jj + 3]),
              pack_bf16(acc[4 * jj + 4], acc[4 * jj + 5]), pack_bf16(acc[4 * jj + 6], acc[4 * jj + 7]));
  }
}

template <bool FIRST>
__device__ __forceinline__ void qproj_tile(int j, uint32_t sb, int g, int lane, uint32_t frag_off, uint32_t (&wr)[NWQ][4],
                                           int& slot, uint32_t& xph) {
  float acc[48];
  const uint32_t bars = sb + OFF_BAR;
  const uint32_t xlo = opaque(desc_lo(sb + OFF_X, 16));
  int prev = 0, prev2 = 0;
  mbar_wait(bars + (B_XFULL + slot) * 8, xph);
  if (!FIRST) named_bar(4 + g, 256);
#pragma unroll
  for (int ks = 0; ks < 8; ++ks) {
    if (FIRST) {
      mbar_wait(bars + (B_WFULL + g * 8 + ks) * 8, 0);
      if ((threadIdx.x & 127) == 0) PROF(208 + g * 8 + ks);
#pragma unroll
      for (int kk = 0; kk < 4; ++kk)
        if (ks * 4 + kk < NWQ) ldsm_x4_t(wr[ks * 4 + kk], sb + (g ? w_stage(1, ks) : w_stage(0, ks)) + kk * 2048 + frag_off);
      if (ks == 2) { __syncwarp(); if (lane == 0) mbar_arrive(bars + (B_WDONE + 1) * 8); }
      if (ks == 7) {
        __syncwarp();
        if (lane == 0) mbar_arrive(bars + B_WDONE * 8);
        if (g == 1 && lane < 2) mbar_arrive_cta(bars + B_WFREE * 8, lane);
      }
    }
    const uint32_t xs = xlo + slot * (X_SLOT >> 4);
    wg_fence();
#pragma unroll
    for (int kk = 0; kk < 4; ++kk) {
      if (ks == 0 && kk == 0)
        wgmma_rs_n96_z(acc, wr[0][0], wr[0][1], wr[0][2], wr[0][3], xs);
      else if (ks * 4 + kk < NWQ)
        wgmma_rs_n96(acc, wr[ks * 4 + kk][0], wr[ks * 4 + kk][1], wr[ks * 4 + kk][2], wr[ks * 4 + kk][3], xs + kk * 2, 1);
      else
        wgmma_ss_n96_ta(acc, xlo + ((OFF_WP - OFF_X + (kk - 2) * 2048) >> 4) + g * 256, xs + kk * 2, 1);
    }
    wg_commit();
    if (ks == PP_HAND && !(FIRST && g == 0) && !(j == 7 && g == 1)) named_arrive(4 + (g ^ 1), 256);
    const int cur = slot;
    if (++slot == X_NS) { slot = 0; xph ^= 1; }
    if (ks < 7) mbar_wait(bars + (B_XFULL + slot) * 8, xph);
    if (ks > 0) {
      wg_wait<1>();
      if (lane < 2) mbar_arrive_cta(bars + (B_XEMPTY + prev) * 8, lane);
    }
    prev = cur;
  }
  wg_wait<0>();
  if (lane < 2) mbar_arrive_cta(bars + (B_XEMPTY + prev) * 8, lane);
  if ((threadIdx.x & 127) == 0) PROF(8 + g * 8 + j);
  const int buf = j & 1;
  if (FIRST) mbar_wait(bars + B_WDONE * 8, 0);
  if (j >= 2) mbar_wait(bars + (B_QEMPTY + buf) * 8, ((j >> 1) - 1) & 1);
  store_acc_T(acc, sb + OFF_QO + buf * QO_BUF + g * 12288 + frag_off);
  fence_async_smem();
  __syncwarp();
  if (lane == 0) mbar_arrive(bars + (B_QFULL + buf) * 8);
}

__device__ __forceinline__ void pv_tile(int j, uint32_t sb, int g, int lane, uint32_t frag_off) {
  float o0[24], o1[24];
  const uint32_t bars = sb + OFF_BAR;
  const uint32_t vlo = desc_lo(sb + OFF_V + g * 6144, 16), plo = desc_lo(sb + OFF_P, 16);
  mbar_wait(bars + B_VFULL * 8, j & 1);
  mbar_wait(bars + B_PFULL * 8, j & 1);
  wg_fence();
#pragma unroll
  for (int kk = 0; kk < 3; ++kk) {
    if (kk == 0) {
      wgmma_ss_n48_ta_z(o0, vlo, plo);
      wgmma_ss_n48_ta_z(o1, vlo + 768, plo + 384);
    } else {
      wgmma_ss_n48_ta(o0, vlo + kk * 128, plo + kk * 2, 1);
      wgmma_ss_n48_ta(o1, vlo + 768 + kk * 128, plo + 384 + kk * 2, 1);
    }
  }
  wg_commit();
  wg_wait<0>();
  if (j == 7) { if (lane < 2) mbar_arrive_cta(bars + B_VDONE * 8, lane); }
  else if (lane == 0) mbar_arrive(bars + B_VEMPTY * 8);
  const int buf = j & 1;
  store_acc_T<6>(o0, sb + OFF_QO + buf * QO_BUF + g * 12288 + frag_off);
  store_acc_T<6>(o1, sb + OFF_QO + buf * QO_BUF + g * 12288 + frag_off + 6144);
  fence_async_smem();
  __syncwarp();
  if (lane == 0) mbar_arrive(bars + (B_OFULL + buf) * 8);
  if ((threadIdx.x & 127) == 0) PROF(24 + g * 8 + j);
}

__device__ __forceinline__ void softmax_exp(float (&s)[24], float& i0, float& i1) {
  const float sc = 0.08838834764831845f * 1.4426950408889634f;
  float m0 = fmaxf(s[0], s[1]), m1 = fmaxf(s[2], s[3]);
#pragma unroll
  for (int i = 1; i < 6; ++i) { m0 = fmaxf(m0, fmaxf(s[4 * i], s[4 * i + 1])); m1 = fmaxf(m1, fmaxf(s[4 * i + 2], s[4 * i + 3])); }
  m0 = fmaxf(m0, __shfl_xor_sync(0xffffffffu, m0, 1)); m1 = fmaxf(m1, __shfl_xor_sync(0xffffffffu, m1, 1));
  m0 = fmaxf(m0, __shfl_xor_sync(0xffffffffu, m0, 2)); m1 = fmaxf(m1, __shfl_xor_sync(0xffffffffu, m1, 2));
  const float b0 = -m0 * sc, b1 = -m1 * sc;
  float l0 = 0.f, l1 = 0.f;
#pragma unroll
  for (int i = 0; i < 6; ++i) {
    s[4 * i] = ex2(fmaf(s[4 * i], sc, b0)); s[4 * i + 1] = ex2(fmaf(s[4 * i + 1], sc, b0));
    s[4 * i + 2] = ex2(fmaf(s[4 * i + 2], sc, b1)); s[4 * i + 3] = ex2(fmaf(s[4 * i + 3], sc, b1));
    l0 += s[4 * i] + s[4 * i + 1]; l1 += s[4 * i + 2] + s[4 * i + 3];
  }
  l0 += __shfl_xor_sync(0xffffffffu, l0, 1); l1 += __shfl_xor_sync(0xffffffffu, l1, 1);
  l0 += __shfl_xor_sync(0xffffffffu, l0, 2); l1 += __shfl_xor_sync(0xffffffffu, l1, 2);
  i0 = __fdividef(1.f, l0); i1 = __fdividef(1.f, l1);
}

__device__ __forceinline__ void issue_scores(float (&s)[24], uint32_t qlo, uint32_t klo) {
#pragma unroll
  for (int kk = 0; kk < 8; ++kk) {
    if (kk == 0) wgmma_ss_n48_z(s, qlo, klo);
    else wgmma_ss_n48(s, qlo + (kk >> 2) * 768 + (kk & 3) * 2, klo + (kk >> 2) * 384 + (kk & 3) * 2, 1);
  }
}
__device__ __forceinline__ void store_p(const float (&s)[24], float i0, float i1, uint32_t a, int lane) {
#pragma unroll
  for (int jj = 0; jj < 6; jj += 2) {
    const int oct = jj + (lane >> 4);
    stsm_x4(a + ((oct ^ (lane & 7)) << 4), pack_bf16(s[4 * jj] * i0, s[4 * jj + 1] * i0), pack_bf16(s[4 * jj + 2] * i1, s[4 * jj + 3] * i1),
            pack_bf16(s[4 * jj + 4] * i0, s[4 * jj + 5] * i0), pack_bf16(s[4 * jj + 6] * i1, s[4 * jj + 7] * i1));
  }
}

__device__ __forceinline__ void load_w(uint32_t sb, const CUtensorMap* m, int head, int ks) {
  const uint64_t pol = policy_evict_first();
#pragma unroll
  for (int g = 0; g < 2; ++g) {
    const uint32_t wb = sb + OFF_BAR + (B_WFULL + g * 8 + ks) * 8;
    const uint32_t d = sb + (ks < 3 ? OFF_K + (ks * 2 + g) * 8192 : (ks < 6 ? OFF_QO + ((ks - 3) * 2 + g) * 8192 : (g ? 98304 : OFF_P) + (ks - 6) * 8192));
    mbar_expect_tx(wb, 8192);
    tma_ld_hint(d, m, head * 128 + g * 64, ks * 64, wb, pol);
    tma_ld_hint(ks == 7 ? sb + OFF_WP + g * 4096 : d + 4096, m, head * 128 + g * 64, ks * 64 + 32, wb, pol);
  }
}

__global__ void __cluster_dims__(2, 1, 1) __launch_bounds__(NTHREADS, 1)
fused_kernel(const __grid_constant__ Params P) {
  extern __shared__ uint8_t smem_raw[];
  const uint32_t sb = (smem_u32(smem_raw) + 1023u) & ~1023u;
  const uint32_t bars = sb + OFF_BAR;
  const int tid = threadIdx.x, warp = tid >> 5, lane = tid & 31;
  const int rank = blockIdx.x & 1;
  const int cid = blockIdx.x >> 1;
  const int br = cid >> 5;
  const int c5 = cid & 31;
  const int pj = c5 >> 1, half = c5 & 1;
  const int head = pj * 2 + rank;
  const int r0 = pj & 3;
  const int T = c5 >> 2, kh = (c5 >> 1) & 1, cs = (c5 & 1) * 2 + rank;

  if (tid == 384) {
    PROF(0);
    asm volatile("prefetch.tensormap [%0];" :: "l"(&P.wq[br]) : "memory");
    for (int i = 0; i < 16; ++i) mbar_init(bars + (B_WFULL + i) * 8, 1);
    asm volatile("fence.mbarrier_init.release.cluster;" ::: "memory");
    fence_async_smem();
  } else if (tid == 0) {
    for (int i = 0; i < X_NS; ++i) { mbar_init(bars + (B_XFULL + i) * 8, 1); mbar_init(bars + (B_XEMPTY + i) * 8, 16); }
    for (int i = 0; i < 2; ++i) { mbar_init(bars + (B_QFULL + i) * 8, 8); mbar_init(bars + (B_QEMPTY + i) * 8, 1); }
    for (int i = 0; i < 2; ++i) { mbar_init(bars + (B_KFULL + i) * 8, 1); mbar_init(bars + (B_VFULL + i) * 8, 1); mbar_init(bars + (B_WDONE + i) * 8, 8); }
    asm volatile("fence.mbarrier_init.release.cluster;" ::: "memory");
  } else if (tid == 32) {
    for (int i = 0; i < P2_NST; ++i) { mbar_init(bars + (B_P2FULL + i) * 8, 1); mbar_init(bars + (B_P2EMPTY + i) * 8, 16); }
    mbar_init(bars + B_KEMPTY * 8, 4);
    mbar_init(bars + B_WFREE * 8, 8);
    mbar_init(bars + B_VEMPTY * 8, 8);
    mbar_init(bars + B_PFULL * 8, 3);
    for (int i = 0; i < 2; ++i) { mbar_init(bars + (B_OFULL + i) * 8, 8); mbar_init(bars + (B_OST + i) * 8, 2); }
    asm volatile("fence.mbarrier_init.release.cluster;" ::: "memory");
  } else if (tid == 64) {
    for (int i = 0; i < 16; ++i) mbar_init(bars + (B_HREADY + i) * 8, 1);
    mbar_init(bars + B_KDONE * 8, 4);
    mbar_init(bars + B_VDONE * 8, 16);
    asm volatile("fence.mbarrier_init.release.cluster;" ::: "memory");
  } else if (tid == 96) {
    l2_prefetch((const char*)P.xp[br] + (size_t)(blockIdx.x & 63) * 24576, 24576);
    asm volatile("prefetch.tensormap [%0];" :: "l"(&P.x[br]) : "memory");
    asm volatile("prefetch.tensormap [%0];" :: "l"(&P.k[br]) : "memory");
    asm volatile("prefetch.tensormap [%0];" :: "l"(&P.v[br]) : "memory");
    asm volatile("prefetch.tensormap [%0];" :: "l"(&P.o) : "memory");
  }
  __syncwarp();
  asm volatile("barrier.cluster.arrive.relaxed.aligned;" ::: "memory");
  if (tid == 384) {
    load_w(sb, &P.wq[br], head, 0);
  }
  __syncwarp();
  asm volatile("barrier.cluster.wait.aligned;" ::: "memory");
  if (tid == 0) PROF(1);

  if (warp < 8) {
    asm volatile("setmaxnreg.inc.sync.aligned.u32 200;");
    const int g = warp >> 2;
    const uint32_t frag_off = ((lane >> 4) * 8 + (lane & 7)) * 128 + (((2 * (warp & 3) + ((lane >> 3) & 1)) ^ (lane & 7)) << 4);
    {
      uint32_t wr[NWQ][4];
      int slot = 0; uint32_t xph = 0;
      qproj_tile<true>(0, sb, g, lane, frag_off, wr, slot, xph);
#pragma unroll 1
      for (int j = 1; j < 8; ++j) {
        qproj_tile<false>(j, sb, g, lane, frag_off, wr, slot, xph);
        pv_tile(j - 1, sb, g, lane, frag_off);
      }
    }
    {
      const int bid = fresh_ctaid(), tid = fresh_tid();
      const int br = bid >> 6, T = (bid >> 3) & 7, kh = (bid >> 2) & 1, cs = bid & 3;
      float accK[48], accS[48];
#pragma unroll
      for (int i = 0; i < 48; ++i) { accK[i] = 0.f; accS[i] = 0.f; }
      int st = 0; uint32_t ph = 0; int prev = 0;
      mbar_wait(bars + B_P2FULL * 8, 0);
#pragma unroll 1
      for (int it = 0; it < 32; ++it) {
        if (tid == 0) PROF(72 + it);
        const uint32_t alo = desc_lo(sb + p2_a(st, g), 16), blo = desc_lo(sb + p2_b(st), 16);
        wg_fence();
#pragma unroll
        for (int kk = 0; kk < 4; ++kk) wgmma_ss_n192_ta(accK, accS, alo + kk * 128, blo + kk * 2, 1);
        wg_commit();
        const int cur = st;
        if (++st == P2_NST) { st = 0; ph ^= 1; }
        if (it == PV7_AT) {
          wg_wait<0>();
          if (lane < 2) { if (it > 0) mbar_arrive_cta(bars + (B_P2EMPTY + prev) * 8, lane); }
          pv_tile(7, sb, g, lane, frag_off);
          mbar_wait(bars + (B_P2FULL + st) * 8, ph);
        } else {
          if (it < 31) mbar_wait(bars + (B_P2FULL + st) * 8, ph);
          if (it > 0) {
            wg_wait<1>();
            if (it <= 27 && lane < 2) mbar_arrive_cta(bars + (B_P2EMPTY + prev) * 8, lane);
          }
        }
        prev = cur;
      }
      const unsigned epoch = (ld_relaxed(&g_done) / NCTA + 1u);
      wg_wait<0>();
      if (tid == 0) PROF(2);
      const uint32_t tag = epoch & 3u;
      uint4* dst = g_part + (size_t)bid * 12 * 256 + tid;
#pragma unroll
      for (int i = 0; i < 12; ++i)
        asm volatile("st.relaxed.gpu.global.v4.b32 [%0], {%1, %2, %3, %4};" :: "l"(dst + i * 256), "r"((__float_as_uint(accS[4 * i]) & ~3u) | tag),
                     "r"((__float_as_uint(accS[4 * i + 1]) & ~3u) | tag), "r"((__float_as_uint(accS[4 * i + 2]) & ~3u) | tag),
                     "r"((__float_as_uint(accS[4 * i + 3]) & ~3u) | tag) : "memory");
      if (tid == 0) PROF(5);
      const uint4* src = g_part + (size_t)(bid ^ 4) * 12 * 256 + tid;
      {
        uint32_t spins = 0;
        while ((ld_relaxed(&src[11 * 256].w) & 3u) != tag) { __nanosleep(40); if (++spins > (1u << 22)) __trap(); }
      }
      {
        uint4 v[12];
        uint32_t spins = 0;
        bool ok;
        do {
#pragma unroll
          for (int i = 0; i < 12; ++i) {
            asm volatile("ld.relaxed.gpu.global.v4.b32 {%0, %1, %2, %3}, [%4];" : "=r"(v[i].x), "=r"(v[i].y), "=r"(v[i].z), "=r"(v[i].w) : "l"(src + i * 256) : "memory");
          }
          uint32_t bad = 0;
#pragma unroll
          for (int i = 0; i < 12; ++i) bad |= (v[i].x ^ tag) | (v[i].y ^ tag) | (v[i].z ^ tag) | (v[i].w ^ tag);
          ok = (bad & 3u) == 0;
          if (++spins > (1u << 22)) __trap();
        } while (!ok);
#pragma unroll
        for (int i = 0; i < 12; ++i) {
          accK[4 * i] += __uint_as_float(v[i].x & ~3u); accK[4 * i + 1] += __uint_as_float(v[i].y & ~3u);
          accK[4 * i + 2] += __uint_as_float(v[i].z & ~3u); accK[4 * i + 3] += __uint_as_float(v[i].w & ~3u);
        }
      }
      if (tid == 0) PROF(3);
      named_bar(1, 256);
      store_acc_T(accK, sb + g * 12288 + frag_off);
      fence_async_smem();
      named_bar(2 + g, 128);
      if ((tid & 127) == 0) {
        tma_st(&P.out_st, br * 512 + cs * 128 + g * 64, T * 192 + kh * 96, sb + g * 12288);
        bulk_commit();
        bulk_wait_read<0>();
        if (tid == 0) {
          PROF(4);
          atomicAdd(&g_done, 1u);
        }
      }
    }
  } else if (warp < 12) {
    asm volatile("setmaxnreg.dec.sync.aligned.u32 88;");
    const int w = warp - 8;
    const uint32_t pa = sb + OFF_P + (16 * w + ((lane >> 3) & 1) * 8 + (lane & 7)) * 128;
    const uint32_t klo = desc_lo(sb + OFF_K, 16);
#pragma unroll 1
    for (int j = 0; j < 8; ++j) {
      const int buf = j & 1;
      const uint32_t qlo = desc_lo(sb + OFF_QO + buf * QO_BUF, 16);
      float sa[24], sb2[24], i0, i1;
      mbar_wait(bars + (B_QFULL + buf) * 8, (j >> 1) & 1);
      mbar_wait(bars + (B_KFULL + 0) * 8, j & 1);
      if (tid == 256) PROF(56 + j);
      wg_fence();
      issue_scores(sa, qlo, klo);
      issue_scores(sb2, qlo + 384, klo + 768);
      wg_commit();
      wg_wait<0>();
      if (lane == 0) mbar_arrive(bars + (j == 7 ? B_KDONE : B_KEMPTY) * 8);
      if (tid == 256) PROF(104 + j);
      float i2, i3;
      softmax_exp(sa, i0, i1);
      softmax_exp(sb2, i2, i3);
      if (j > 0) mbar_wait(bars + B_VEMPTY * 8, (j - 1) & 1);
      if (w < 3) {
        store_p(sa, i0, i1, pa, lane);
        store_p(sb2, i2, i3, pa + 6144, lane);
        fence_async_smem();
        __syncwarp();
        if (lane == 0) mbar_arrive(bars + B_PFULL * 8);
      }
      if (tid == 256) PROF(40 + j);
    }
  } else {
    asm volatile("setmaxnreg.dec.sync.aligned.u32 24;");
    auto tile_of = [&](int j) { return half * 8 + ((((r0 + (j >> 1)) & 3) << 1) | (j & 1)); };
    if (tid == 416) {
      uint64_t pol;
      asm volatile("createpolicy.fractional.L2::evict_first.b64 %0, 1.0;" : "=l"(pol));
      auto prefetch_kv = [&](int n) {
        const size_t off = (size_t)((tile_of(n >> 1) * 2 + (n & 1)) * 32 + head) * 6144;
        l2_prefetch_hint(P.kp[br] + off, 12288, pol);
        l2_prefetch_hint(P.vp[br] + off, 12288, pol);
      };
      if (PF_START >= 0) mbar_wait(bars + (B_WFULL + (PF_START >= 0 ? PF_START : 0)) * 8, 0);
      for (int n = 2; n < PF_DIST; ++n) prefetch_kv(n);
      mbar_wait(bars + (B_WDONE + 1) * 8, 0);
      int kj = 0, vj = 0;
      uint32_t spins = 0;
      while (kj < 8 || vj < 8) {
        if (kj < 8 && (kj == 0 || mbar_test(bars + B_KEMPTY * 8, (kj - 1) & 1))) {
          for (int sub = 0; sub < 2; ++sub) {
            const int row = DBG_KVSAME ? (sub * 32 + head) * 48 : ((tile_of(kj) * 2 + sub) * 32 + head) * 48;
            const uint32_t kbar = bars + B_KFULL * 8, kd = sb + OFF_K + sub * 12288;
            if (sub == 0) mbar_expect_tx(kbar, 24576);
            tma_ld_hint(kd, &P.k[br], 0, row, kbar, pol);
            tma_ld_hint(kd + 6144, &P.k[br], 64, row, kbar, pol);
          }
          for (int sub = 0; sub < 2; ++sub) {
            const int pn = 2 * kj + sub - 2 + PF_DIST;
            if (PF_DIST > 0 && kj >= 1 && pn < 16) prefetch_kv(pn);
          }
          ++kj;
        }
        if (vj < 8 && (vj == 0 || mbar_test(bars + B_VEMPTY * 8, (vj - 1) & 1))) {
          for (int sub = 0; sub < 2; ++sub) {
            const int row = DBG_KVSAME ? (sub * 32 + head) * 48 : ((tile_of(vj) * 2 + sub) * 32 + head) * 48;
            const uint32_t vbar = bars + B_VFULL * 8, vd = sb + OFF_V + sub * 12288;
            if (sub == 0) mbar_expect_tx(vbar, 24576);
            tma_ld_hint(vd, &P.v[br], 0, row, vbar, pol);
            tma_ld_hint(vd + 6144, &P.v[br], 64, row, vbar, pol);
          }
          ++vj;
        }
        __nanosleep(20);
        if (++spins > (1u << 24)) __trap();
      }
    } else if (tid == 448) {
      const unsigned epoch = ld_relaxed(&g_done) / NCTA + 1u;
      for (int j = 0; j < 8; ++j) {
        const int buf = j & 1;
        mbar_wait(bars + (B_OFULL + buf) * 8, (j >> 1) & 1);
        const int t = tile_of(j);
        const uint32_t qb = sb + OFF_QO + buf * QO_BUF;
        tma_st(&P.o, head * 128, br * 1536 + t * 96, qb);
        tma_st(&P.o, head * 128 + 64, br * 1536 + t * 96, qb + 12288);
        bulk_commit();
        bulk_wait_read<0>();
        mbar_arrive(bars + (B_QEMPTY + buf) * 8);
        if (j >= 6) { mbar_arrive_cta(bars + (B_OST + j - 6) * 8, 0); mbar_arrive_cta(bars + (B_OST + j - 6) * 8, 1); }
        bulk_wait<0>();
        st_relaxed(&g_oflag[(br * 16 + t) * 32 + head], epoch);
      }
    } else if (warp == 15) {
      const unsigned epoch = ld_relaxed(&g_done) / NCTA + 1u;
      const int q = (lane >> 2) & 3, hi = lane & 3;
      const int h2 = (kh * 8 + (hi >> 1) * 4 + (((T & 3) - q) & 3)) * 2 + (hi & 1);
      const unsigned* fp = &g_oflag[(br * 16 + T * 2 + rank) * 32 + h2];
      bool done = lane >= 16;
      uint32_t it = 0;
      while (!__all_sync(0xffffffffu, done)) {
        if (!done && ld_relaxed(fp) == epoch) { mbar_arrive(bars + (B_HREADY + lane) * 8); done = true; }
        __nanosleep(200);
        if (++it > (1u << 22)) __trap();
      }
    } else if (tid == 384) {
      int slot = 0; uint32_t ph = 1;
      for (int j = 0; j < 8; ++j) {
        const int xrow = tile_of(j) * 96;
        for (int ks = 0; ks < 8; ++ks) {
          if (j == 1 && ks == 0) mbar_wait(bars + B_WFREE * 8, 0);
          mbar_wait(bars + (B_XEMPTY + slot) * 8, ph);
          const uint32_t xb = bars + (B_XFULL + slot) * 8;
          mbar_expect_tx(xb, X_SLOT);
          if (j == 4 || j == 5) PROF(192 + (j - 4) * 8 + ks);
          if ((ks & 1) == rank) tma_ld_mc(sb + OFF_X + slot * X_SLOT, &P.x[br], ks * 64, xrow, xb);
          if (++slot == X_NS) { slot = 0; ph ^= 1; }
          if (j == 0 && ks < 7) load_w(sb, &P.wq[br], head, ks + 1);
        }
        if (WO_PF_ON && j >= WO_PF && j < WO_PF + 4)
          l2_prefetch((const char*)P.wop[br] + (size_t)(blockIdx.x & 63) * 65536 + (j - WO_PF) * 16384, 16384);
        if (j == 6) {
          asm volatile("prefetch.tensormap [%0];" :: "l"(&P.wo[br]) : "memory");
          asm volatile("prefetch.tensormap [%0];" :: "l"(&P.out_st) : "memory");
        }
      }
      const int Tq = T & 3;
      const uint64_t pol2 = policy_evict_first();
      const int orow = br * 1536 + T * 192 + rank * 96;
      const uint32_t odst = (rank == kh) ? 0 : 12288;
      const uint32_t xph = ph;
      int st = 0; ph = 0;
      for (int it = 0; it < 32; ++it) {
        const int q = it >> 3, hi = (it >> 1) & 3;
        const int h2 = (kh * 8 + (hi >> 1) * 4 + ((Tq - q) & 3)) * 2 + (hi & 1);
        const int k0 = h2 * 128 + (it & 1) * 64;
        if (it < P2_NST) {
          if (it < 2) {
            for (int i = 0; i < 4; ++i) { mbar_wait(bars + (B_XEMPTY + slot) * 8, xph); ++slot; }
          } else if (it == 2) { mbar_wait(bars + B_KDONE * 8, 0); mbar_wait(bars + B_OST * 8, 0); }
          else if (it == 3) mbar_wait(bars + B_VDONE * 8, 0);
          else mbar_wait(bars + (B_OST + 1) * 8, 0);
        } else {
          mbar_wait(bars + (B_P2EMPTY + st) * 8, ph ^ 1);
        }
        PROF(128 + it);
        const uint32_t fb = bars + (B_P2FULL + st) * 8;
        mbar_expect_tx(fb, 40960);
        if (EF_WO) { tma_ld_hint(sb + p2_a(st, 0), &P.wo[br], cs * 128, k0, fb, pol2); tma_ld_hint(sb + p2_a(st, 1), &P.wo[br], cs * 128 + 64, k0, fb, pol2); }
        else { tma_ld(sb + p2_a(st, 0), &P.wo[br], cs * 128, k0, fb); tma_ld(sb + p2_a(st, 1), &P.wo[br], cs * 128 + 64, k0, fb); }
        if ((it & 1) == 0) { mbar_wait(bars + (B_HREADY + (it >> 1)) * 8, 0); asm volatile("fence.proxy.async.global;" ::: "memory"); }
        PROF(160 + it);
        if (EF_O) tma_ld_mc_hint(sb + p2_b(st) + odst, &P.o, k0, orow, fb, pol2); else tma_ld_mc(sb + p2_b(st) + odst, &P.o, k0, orow, fb);
        if (++st == P2_NST) { st = 0; ph ^= 1; }
      }
    }
  }
}

typedef CUresult (*EncodeFn)(CUtensorMap*, CUtensorMapDataType, cuuint32_t, void*, const cuuint64_t*, const cuuint64_t*,
                             const cuuint32_t*, const cuuint32_t*, CUtensorMapInterleave, CUtensorMapSwizzle,
                             CUtensorMapL2promotion, CUtensorMapFloatOOBfill);

static void make_map(EncodeFn enc, CUtensorMap* m, const void* ptr, uint64_t cols, uint64_t rows, uint32_t box_rows) {
  cuuint64_t gdim[2] = {cols, rows};
  cuuint64_t gstr[1] = {cols * 2};
  cuuint32_t box[2] = {64, box_rows};
  cuuint32_t es[2] = {1, 1};
  enc(m, CU_TENSOR_MAP_DATA_TYPE_BFLOAT16, 2, const_cast<void*>(ptr), gdim, gstr, box, es, CU_TENSOR_MAP_INTERLEAVE_NONE,
      CU_TENSOR_MAP_SWIZZLE_128B, CU_TENSOR_MAP_L2_PROMOTION_L2_128B, CU_TENSOR_MAP_FLOAT_OOB_FILL_NONE);
}

}

extern "C" void kernel_launch(void* const* d_in, const int* in_sizes, int n_in, void* d_out, int out_size) {
  using namespace fk;
  (void)in_sizes; (void)n_in; (void)out_size;
  static EncodeFn enc = nullptr;
  static void* o_ptr = nullptr;
  if (!enc) {
    cudaDriverEntryPointQueryResult qr;
    cudaGetDriverEntryPoint("cuTensorMapEncodeTiled", (void**)&enc, cudaEnableDefault, &qr);
    cudaGetSymbolAddress(&o_ptr, g_O);
    cudaFuncSetAttribute(fused_kernel, cudaFuncAttributeMaxDynamicSharedMemorySize, SMEM_BYTES);
  }
  Params P;
  for (int b = 0; b < 2; ++b) {
    make_map(enc, &P.x[b], d_in[5 * b + 0], 512, 1536, 96);
    make_map(enc, &P.k[b], d_in[5 * b + 1], 128, 32 * 32 * 48, 48);
    make_map(enc, &P.v[b], d_in[5 * b + 2], 128, 32 * 32 * 48, 48);
    make_map(enc, &P.wq[b], d_in[5 * b + 3], 4096, 512, 32);
    make_map(enc, &P.wo[b], d_in[5 * b + 4], 512, 4096, 64);
    P.kp[b] = (const __nv_bfloat16*)d_in[5 * b + 1];
    P.vp[b] = (const __nv_bfloat16*)d_in[5 * b + 2];
    P.wop[b] = (const __nv_bfloat16*)d_in[5 * b + 4];
    P.xp[b] = (const __nv_bfloat16*)d_in[5 * b + 0];
  }
  make_map(enc, &P.o, o_ptr, 4096, 3072, 96);
  make_map(enc, &P.out_st, d_out, 1024, 1536, 96);
  fused_kernel<<<NCTA, NTHREADS, SMEM_BYTES, cudaStreamPerThread>>>(P);
}
```

```cpp
#include <cuda_runtime.h>
#include <cuda_bf16.h>
#include <cuda.h>
#include <stdint.h>

#define GGROUP 4
#define GPEND 1
#define PF_DIST 0
#define PF_START 11
#define PINGPONG 1
#define PP_HAND 3
#define WO_PF 3
#define WO_PF_ON 0
#define PV7_AT 1
#define EF_WO 0
#define EF_O 1
#define DBG_NOKV 0
#define DBG_KVSAME 0
#define QDEPTH 1
#define DBG_NOP 0
#define DBG_NOS 0
#define DBG_NOEPI 0
#define DBG_NOX 0
#define SEND_PER 4
#define PF_LAST 99
#define PF_E0 0
#define PF_E1 0
#define KORDER 1
namespace fk {

constexpr int NTHREADS = 512;
constexpr int NCTA = 128;

constexpr int X_SLOT   = 12288;
constexpr int X_NS     = 9;
constexpr int OFF_X    = 0;
constexpr int QO_BUF   = 24576;
constexpr int OFF_QO   = 118784;
constexpr int OFF_K    = 167936;
constexpr int OFF_V    = 192512;
constexpr int OFF_P    = 217088;
constexpr int OFF_WP   = 110592;
constexpr int P2_NST   = 5;
constexpr int P2_TAIL  = 4;
constexpr int P2_FULL  = 32 - P2_TAIL;
constexpr int P2_ITS   = 32 + P2_TAIL;
constexpr int OFF_BAR  = 229376;
constexpr int SMEM_BYTES = OFF_BAR + 768 + 1024 + 1024;
constexpr int NWQ = 30;

__device__ __forceinline__ constexpr uint32_t w_stage(int g, int ks) {
  return ks < 3 ? OFF_K + (ks * 2 + g) * 8192 : (ks < 6 ? OFF_QO + ((ks - 3) * 2 + g) * 8192 : (g ? 98304 : OFF_P) + (ks - 6) * 8192);
}
__device__ __forceinline__ uint32_t p2_a(int st, int g) {
  return st == 0 ? 12288 + g * 8192 : st == 1 ? 53248 + g * 8192 : st == 2 ? OFF_K + g * 8192 : st == 3 ? (g ? OFF_K + 16384 : 0) : OFF_V + g * 8192;
}
__device__ __forceinline__ uint32_t p2_b(int st) {
  return st == 0 ? 28672 : st == 1 ? 69632 : st == 2 ? OFF_QO : st == 3 ? 94208 : OFF_QO + QO_BUF;
}

__device__ __forceinline__ int k_order(int q, int Tq) {
  return (Tq == 3 && q < 2) ? 1 - q : q;
}

constexpr int B_XFULL = 0, B_XEMPTY = 9, B_WFULL = 18, B_QFULL = 34, B_QEMPTY = 36, B_KFULL = 38, B_VFULL = 40,
              B_P2FULL = 42, B_P2EMPTY = 47, B_WDONE = 52, B_KEMPTY = 54, B_WFREE = 55, B_VEMPTY = 56, B_PFULL = 57, B_OFULL = 58,
              B_OST = 60, B_KDONE = 62, B_VDONE = 63, B_HREADY = 64;

struct __align__(64) Params {
  CUtensorMap x[2], wq[2], k[2], v[2], wo[2], o, out_st;
  const __nv_bfloat16* kp[2];
  const __nv_bfloat16* vp[2];
  const __nv_bfloat16* wop[2];
  const __nv_bfloat16* xp[2];
};

__device__ __nv_bfloat16 g_O[3072 * 4096];
__device__ uint4 g_part[NCTA * 12 * 256];
__device__ unsigned g_oflag[2 * 16 * 32];
__device__ unsigned g_done;

#define PROF(idx) do {} while (0)
__device__ __forceinline__ uint32_t smem_u32(const void* p) { return (uint32_t)__cvta_generic_to_shared(p); }
__device__ __forceinline__ void mbar_init(uint32_t bar, int cnt) { asm volatile("mbarrier.init.shared::cta.b64 [%0], %1;" :: "r"(bar), "r"(cnt) : "memory"); }
__device__ __forceinline__ void mbar_expect_tx(uint32_t bar, uint32_t bytes) { asm volatile("mbarrier.arrive.expect_tx.shared::cta.b64 _, [%0], %1;" :: "r"(bar), "r"(bytes) : "memory"); }
__device__ __forceinline__ void mbar_arrive(uint32_t bar) { asm volatile("mbarrier.arrive.shared::cta.b64 _, [%0];" :: "r"(bar) : "memory"); }
__device__ __forceinline__ void mbar_arrive_cta(uint32_t bar, uint32_t cta) {
  asm volatile("{\n.reg .b32 r;\nmapa.shared::cluster.u32 r, %0, %1;\nmbarrier.arrive.shared::cluster.b64 _, [r];\n}\n" :: "r"(bar), "r"(cta) : "memory");
}
__device__ __forceinline__ uint32_t mbar_try(uint32_t bar, uint32_t parity) {
  uint32_t ok;
  asm volatile("{\n.reg .pred p;\nmbarrier.try_wait.parity.shared::cta.b64 p, [%1], %2;\nselp.u32 %0, 1, 0, p;\n}\n" : "=r"(ok) : "r"(bar), "r"(parity) : "memory");
  return ok;
}
__device__ __forceinline__ void mbar_wait(uint32_t bar, uint32_t parity) {
  if (mbar_try(bar, parity)) return;
  uint32_t it = 0;
  while (!mbar_try(bar, parity)) { if (++it > (1u << 22)) __trap(); }
}
__device__ __forceinline__ void tma_ld(uint32_t dst, const CUtensorMap* m, int c0, int c1, uint32_t bar) {
  asm volatile("cp.async.bulk.tensor.2d.shared::cluster.global.mbarrier::complete_tx::bytes [%0], [%1, {%3, %4}], [%2];"
               :: "r"(dst), "l"(m), "r"(bar), "r"(c0), "r"(c1) : "memory");
}
__device__ __forceinline__ void tma_ld_hint(uint32_t dst, const CUtensorMap* m, int c0, int c1, uint32_t bar, uint64_t pol) {
  asm volatile("cp.async.bulk.tensor.2d.shared::cluster.global.mbarrier::complete_tx::bytes.L2::cache_hint [%0], [%1, {%3, %4}], [%2], %5;"
               :: "r"(dst), "l"(m), "r"(bar), "r"(c0), "r"(c1), "l"(pol) : "memory");
}
__device__ __forceinline__ void tma_ld_mc(uint32_t dst, const CUtensorMap* m, int c0, int c1, uint32_t bar) {
  asm volatile("cp.async.bulk.tensor.2d.shared::cluster.global.mbarrier::complete_tx::bytes.multicast::cluster [%0], [%1, {%3, %4}], [%2], %5;"
               :: "r"(dst), "l"(m), "r"(bar), "r"(c0), "r"(c1), "h"((uint16_t)3) : "memory");
}
__device__ __forceinline__ void tma_ld_mc_hint(uint32_t dst, const CUtensorMap* m, int c0, int c1, uint32_t bar, uint64_t pol) {
  asm volatile("cp.async.bulk.tensor.2d.shared::cluster.global.mbarrier::complete_tx::bytes.multicast::cluster.L2::cache_hint [%0], [%1, {%3, %4}], [%2], %5, %6;"
               :: "r"(dst), "l"(m), "r"(bar), "r"(c0), "r"(c1), "h"((uint16_t)3), "l"(pol) : "memory");
}
__device__ __forceinline__ void tma_st_hint(const CUtensorMap* m, int c0, int c1, uint32_t src, uint64_t pol) {
  asm volatile("cp.async.bulk.tensor.2d.global.shared::cta.bulk_group.L2::cache_hint [%0, {%2, %3}], [%1], %4;" :: "l"(m), "r"(src), "r"(c0), "r"(c1), "l"(pol) : "memory");
}
__device__ __forceinline__ void tma_st(const CUtensorMap* m, int c0, int c1, uint32_t src) {
  asm volatile("cp.async.bulk.tensor.2d.global.shared::cta.bulk_group [%0, {%2, %3}], [%1];" :: "l"(m), "r"(src), "r"(c0), "r"(c1) : "memory");
}
__device__ __forceinline__ void bulk_commit() { asm volatile("cp.async.bulk.commit_group;" ::: "memory"); }
template <int N> __device__ __forceinline__ void bulk_wait_read() { asm volatile("cp.async.bulk.wait_group.read %0;" :: "n"(N) : "memory"); }
template <int N> __device__ __forceinline__ void bulk_wait() { asm volatile("cp.async.bulk.wait_group %0;" :: "n"(N) : "memory"); }
__device__ __forceinline__ void l2_prefetch(const void* p, uint32_t bytes) { asm volatile("cp.async.bulk.prefetch.L2.global [%0], %1;" :: "l"(p), "r"(bytes) : "memory"); }
__device__ __forceinline__ void l2_prefetch_hint(const void* p, uint32_t bytes, uint64_t pol) { asm volatile("cp.async.bulk.prefetch.L2.global.L2::cache_hint [%0], %1, %2;" :: "l"(p), "r"(bytes), "l"(pol) : "memory"); }
__device__ __forceinline__ uint64_t policy_evict_first() { uint64_t pol; asm volatile("createpolicy.fractional.L2::evict_first.b64 %0, 1.0;" : "=l"(pol)); return pol; }
__device__ __forceinline__ void fence_async_smem() { asm volatile("fence.proxy.async.shared::cta;" ::: "memory"); }
__device__ __forceinline__ void fence_async_all() { asm volatile("fence.proxy.async;" ::: "memory"); }
__device__ __forceinline__ void wg_fence() { asm volatile("wgmma.fence.sync.aligned;" ::: "memory"); }
__device__ __forceinline__ void wg_commit() { asm volatile("wgmma.commit_group.sync.aligned;" ::: "memory"); }
template <int N> __device__ __forceinline__ void wg_wait() { asm volatile("wgmma.wait_group.sync.aligned %0;" :: "n"(N) : "memory"); }
__device__ __forceinline__ void cluster_sync() { asm volatile("barrier.cluster.arrive.relaxed.aligned;\nbarrier.cluster.wait.aligned;\n" ::: "memory"); }
__device__ __forceinline__ void named_arrive(int id, int n) { asm volatile("bar.arrive %0, %1;" :: "r"(id), "r"(n) : "memory"); }
__device__ __forceinline__ uint32_t mbar_test(uint32_t bar, uint32_t parity) {
  uint32_t ok;
  asm volatile("{\n.reg .pred p;\nmbarrier.test_wait.parity.shared::cta.b64 p, [%1], %2;\nselp.u32 %0, 1, 0, p;\n}\n" : "=r"(ok) : "r"(bar), "r"(parity) : "memory");
  return ok;
}
__device__ __forceinline__ void named_bar(int id, int n) { asm volatile("bar.sync %0, %1;" :: "r"(id), "r"(n) : "memory"); }
__device__ __forceinline__ uint32_t desc_lo(uint32_t addr, uint32_t lbo) { return ((addr & 0x3FFFF) >> 4) | ((lbo >> 4) << 16); }
__device__ __forceinline__ uint32_t opaque(uint32_t v) { asm volatile("mov.u32 %0, %0;" : "+r"(v)); return v; }
__device__ __forceinline__ uint32_t pack_bf16(float lo, float hi) {
  uint32_t r; asm("cvt.rn.bf16x2.f32 %0, %1, %2;" : "=r"(r) : "f"(hi), "f"(lo)); return r;
}
__device__ __forceinline__ void ldsm_x4_t(uint32_t (&r)[4], uint32_t addr) {
  asm volatile("ldmatrix.sync.aligned.m8n8.x4.trans.shared.b16 {%0,%1,%2,%3}, [%4];" : "=r"(r[0]), "=r"(r[1]), "=r"(r[2]), "=r"(r[3]) : "r"(addr) : "memory");
}
__device__ __forceinline__ void stsm_x4_t(uint32_t addr, uint32_t a, uint32_t b, uint32_t c, uint32_t d) {
  asm volatile("stmatrix.sync.aligned.m8n8.x4.trans.shared.b16 [%0], {%1,%2,%3,%4};" :: "r"(addr), "r"(a), "r"(b), "r"(c), "r"(d) : "memory");
}
__device__ __forceinline__ void stsm_x4(uint32_t addr, uint32_t a, uint32_t b, uint32_t c, uint32_t d) {
  asm volatile("stmatrix.sync.aligned.m8n8.x4.shared.b16 [%0], {%1,%2,%3,%4};" :: "r"(addr), "r"(a), "r"(b), "r"(c), "r"(d) : "memory");
}
__device__ __forceinline__ unsigned ld_acquire(const unsigned* p) { unsigned v; asm volatile("ld.acquire.gpu.global.u32 %0, [%1];" : "=r"(v) : "l"(p) : "memory"); return v; }
__device__ __forceinline__ unsigned ld_relaxed(const unsigned* p) { unsigned v; asm volatile("ld.relaxed.gpu.global.u32 %0, [%1];" : "=r"(v) : "l"(p) : "memory"); return v; }
__device__ __forceinline__ void st_relaxed(unsigned* p, unsigned v) { asm volatile("st.relaxed.gpu.global.u32 [%0], %1;" :: "l"(p), "r"(v) : "memory"); }
__device__ __forceinline__ void st_release(unsigned* p, unsigned v) { asm volatile("st.release.gpu.global.u32 [%0], %1;" :: "l"(p), "r"(v) : "memory"); }
__device__ __forceinline__ void flag_wait(const unsigned* p, unsigned epoch) {
  uint32_t it = 0;
  while (ld_acquire(p) != epoch) { if (++it > (1u << 24)) __trap(); }
}
__device__ __forceinline__ int fresh_ctaid() { int v; asm volatile("mov.u32 %0, %%ctaid.x;" : "=r"(v)); return v; }
__device__ __forceinline__ int fresh_tid() { int v; asm volatile("mov.u32 %0, %%tid.x;" : "=r"(v)); return v; }
__device__ __forceinline__ unsigned lds_u32(uint32_t a) { unsigned v; asm volatile("ld.shared.u32 %0, [%1];" : "=r"(v) : "r"(a) : "memory"); return v; }
__device__ __forceinline__ float ex2(float x) { float y; asm("ex2.approx.ftz.f32 %0, %1;" : "=f"(y) : "f"(x)); return y; }

__device__ __forceinline__ void wgmma_rs_n96_z(float (&d)[48], uint32_t a0, uint32_t a1, uint32_t a2, uint32_t a3, uint32_t db) {
  asm volatile("{\n.reg .pred p;\n.reg .b64 db;\nsetp.ne.b32 p, 0, 0;\nmov.b64 db, {%52, 0x40000040};\n"
    "wgmma.mma_async.sync.aligned.m64n96k16.f32.bf16.bf16 {%0, %1, %2, %3, %4, %5, %6, %7, %8, %9, %10, %11, %12, %13, %14, %15, %16, %17, %18, %19, %20, %21, %22, %23, %24, %25, %26, %27, %28, %29, %30, %31, %32, %33, %34, %35, %36, %37, %38, %39, %40, %41, %42, %43, %44, %45, %46, %47}, {%48, %49, %50, %51}, db, p, 1, 1, 0;\n}\n"
    : "=f"(d[0]), "=f"(d[1]), "=f"(d[2]), "=f"(d[3]), "=f"(d[4]), "=f"(d[5]), "=f"(d[6]), "=f"(d[7]), "=f"(d[8]), "=f"(d[9]), "=f"(d[10]), "=f"(d[11]), "=f"(d[12]), "=f"(d[13]), "=f"(d[14]), "=f"(d[15]), "=f"(d[16]), "=f"(d[17]), "=f"(d[18]), "=f"(d[19]), "=f"(d[20]), "=f"(d[21]), "=f"(d[22]), "=f"(d[23]), "=f"(d[24]), "=f"(d[25]), "=f"(d[26]), "=f"(d[27]), "=f"(d[28]), "=f"(d[29]), "=f"(d[30]), "=f"(d[31]), "=f"(d[32]), "=f"(d[33]), "=f"(d[34]), "=f"(d[35]), "=f"(d[36]), "=f"(d[37]), "=f"(d[38]), "=f"(d[39]), "=f"(d[40]), "=f"(d[41]), "=f"(d[42]), "=f"(d[43]), "=f"(d[44]), "=f"(d[45]), "=f"(d[46]), "=f"(d[47])
    : "r"(a0), "r"(a1), "r"(a2), "r"(a3), "r"(db));
}

__device__ __forceinline__ void wgmma_ss_n48_z(float (&d)[24], uint32_t da, uint32_t db) {
  asm volatile("{\n.reg .pred p;\n.reg .b64 da, db;\nsetp.ne.b32 p, 0, 0;\nmov.b64 da, {%24, 0x40000040};\nmov.b64 db, {%25, 0x40000040};\n"
    "wgmma.mma_async.sync.aligned.m64n48k16.f32.bf16.bf16 {%0, %1, %2, %3, %4, %5, %6, %7, %8, %9, %10, %11, %12, %13, %14, %15, %16, %17, %18, %19, %20, %21, %22, %23}, da, db, p, 1, 1, 0, 0;\n}\n"
    : "=f"(d[0]), "=f"(d[1]), "=f"(d[2]), "=f"(d[3]), "=f"(d[4]), "=f"(d[5]), "=f"(d[6]), "=f"(d[7]), "=f"(d[8]), "=f"(d[9]), "=f"(d[10]), "=f"(d[11]), "=f"(d[12]), "=f"(d[13]), "=f"(d[14]), "=f"(d[15]), "=f"(d[16]), "=f"(d[17]), "=f"(d[18]), "=f"(d[19]), "=f"(d[20]), "=f"(d[21]), "=f"(d[22]), "=f"(d[23])
    : "r"(da), "r"(db));
}

__device__ __forceinline__ void wgmma_ss_n48_ta_z(float (&d)[24], uint32_t da, uint32_t db) {
  asm volatile("{\n.reg .pred p;\n.reg .b64 da, db;\nsetp.ne.b32 p, 0, 0;\nmov.b64 da, {%24, 0x40000040};\nmov.b64 db, {%25, 0x40000040};\n"
    "wgmma.mma_async.sync.aligned.m64n48k16.f32.bf16.bf16 {%0, %1, %2, %3, %4, %5, %6, %7, %8, %9, %10, %11, %12, %13, %14, %15, %16, %17, %18, %19, %20, %21, %22, %23}, da, db, p, 1, 1, 1, 0;\n}\n"
    : "=f"(d[0]), "=f"(d[1]), "=f"(d[2]), "=f"(d[3]), "=f"(d[4]), "=f"(d[5]), "=f"(d[6]), "=f"(d[7]), "=f"(d[8]), "=f"(d[9]), "=f"(d[10]), "=f"(d[11]), "=f"(d[12]), "=f"(d[13]), "=f"(d[14]), "=f"(d[15]), "=f"(d[16]), "=f"(d[17]), "=f"(d[18]), "=f"(d[19]), "=f"(d[20]), "=f"(d[21]), "=f"(d[22]), "=f"(d[23])
    : "r"(da), "r"(db));
}

__device__ __forceinline__ void wgmma_rs_n96(float (&d)[48], uint32_t a0, uint32_t a1, uint32_t a2, uint32_t a3, uint32_t db, int scale_d) {
  asm volatile("{\n.reg .pred p;\n.reg .b64 db;\nsetp.ne.b32 p, %53, 0;\nmov.b64 db, {%52, 0x40000040};\n"
    "wgmma.mma_async.sync.aligned.m64n96k16.f32.bf16.bf16 {%0, %1, %2, %3, %4, %5, %6, %7, %8, %9, %10, %11, %12, %13, %14, %15, %16, %17, %18, %19, %20, %21, %22, %23, %24, %25, %26, %27, %28, %29, %30, %31, %32, %33, %34, %35, %36, %37, %38, %39, %40, %41, %42, %43, %44, %45, %46, %47}, {%48, %49, %50, %51}, db, p, 1, 1, 0;\n}\n"
    : "+f"(d[0]), "+f"(d[1]), "+f"(d[2]), "+f"(d[3]), "+f"(d[4]), "+f"(d[5]), "+f"(d[6]), "+f"(d[7]), "+f"(d[8]), "+f"(d[9]), "+f"(d[10]), "+f"(d[11]), "+f"(d[12]), "+f"(d[13]), "+f"(d[14]), "+f"(d[15]), "+f"(d[16]), "+f"(d[17]), "+f"(d[18]), "+f"(d[19]), "+f"(d[20]), "+f"(d[21]), "+f"(d[22]), "+f"(d[23]), "+f"(d[24]), "+f"(d[25]), "+f"(d[26]), "+f"(d[27]), "+f"(d[28]), "+f"(d[29]), "+f"(d[30]), "+f"(d[31]), "+f"(d[32]), "+f"(d[33]), "+f"(d[34]), "+f"(d[35]), "+f"(d[36]), "+f"(d[37]), "+f"(d[38]), "+f"(d[39]), "+f"(d[40]), "+f"(d[41]), "+f"(d[42]), "+f"(d[43]), "+f"(d[44]), "+f"(d[45]), "+f"(d[46]), "+f"(d[47])
    : "r"(a0), "r"(a1), "r"(a2), "r"(a3), "r"(db), "r"(scale_d));
}

__device__ __forceinline__ void wgmma_ss_n96_ta(float (&d)[48], uint32_t da, uint32_t db, int scale_d) {
  asm volatile("{\n.reg .pred p;\n.reg .b64 da, db;\nsetp.ne.b32 p, %50, 0;\nmov.b64 da, {%48, 0x40000040};\nmov.b64 db, {%49, 0x40000040};\n"
    "wgmma.mma_async.sync.aligned.m64n96k16.f32.bf16.bf16 {%0, %1, %2, %3, %4, %5, %6, %7, %8, %9, %10, %11, %12, %13, %14, %15, %16, %17, %18, %19, %20, %21, %22, %23, %24, %25, %26, %27, %28, %29, %30, %31, %32, %33, %34, %35, %36, %37, %38, %39, %40, %41, %42, %43, %44, %45, %46, %47}, da, db, p, 1, 1, 1, 0;\n}\n"
    : "+f"(d[0]), "+f"(d[1]), "+f"(d[2]), "+f"(d[3]), "+f"(d[4]), "+f"(d[5]), "+f"(d[6]), "+f"(d[7]), "+f"(d[8]), "+f"(d[9]), "+f"(d[10]), "+f"(d[11]), "+f"(d[12]), "+f"(d[13]), "+f"(d[14]), "+f"(d[15]), "+f"(d[16]), "+f"(d[17]), "+f"(d[18]), "+f"(d[19]), "+f"(d[20]), "+f"(d[21]), "+f"(d[22]), "+f"(d[23]), "+f"(d[24]), "+f"(d[25]), "+f"(d[26]), "+f"(d[27]), "+f"(d[28]), "+f"(d[29]), "+f"(d[30]), "+f"(d[31]), "+f"(d[32]), "+f"(d[33]), "+f"(d[34]), "+f"(d[35]), "+f"(d[36]), "+f"(d[37]), "+f"(d[38]), "+f"(d[39]), "+f"(d[40]), "+f"(d[41]), "+f"(d[42]), "+f"(d[43]), "+f"(d[44]), "+f"(d[45]), "+f"(d[46]), "+f"(d[47])
    : "r"(da), "r"(db), "r"(scale_d));
}

__device__ __forceinline__ void wgmma_ss_n48(float (&d)[24], uint32_t da, uint32_t db, int scale_d) {
  asm volatile("{\n.reg .pred p;\n.reg .b64 da, db;\nsetp.ne.b32 p, %26, 0;\nmov.b64 da, {%24, 0x40000040};\nmov.b64 db, {%25, 0x40000040};\n"
    "wgmma.mma_async.sync.aligned.m64n48k16.f32.bf16.bf16 {%0, %1, %2, %3, %4, %5, %6, %7, %8, %9, %10, %11, %12, %13, %14, %15, %16, %17, %18, %19, %20, %21, %22, %23}, da, db, p, 1, 1, 0, 0;\n}\n"
    : "+f"(d[0]), "+f"(d[1]), "+f"(d[2]), "+f"(d[3]), "+f"(d[4]), "+f"(d[5]), "+f"(d[6]), "+f"(d[7]), "+f"(d[8]), "+f"(d[9]), "+f"(d[10]), "+f"(d[11]), "+f"(d[12]), "+f"(d[13]), "+f"(d[14]), "+f"(d[15]), "+f"(d[16]), "+f"(d[17]), "+f"(d[18]), "+f"(d[19]), "+f"(d[20]), "+f"(d[21]), "+f"(d[22]), "+f"(d[23])
    : "r"(da), "r"(db), "r"(scale_d));
}

__device__ __forceinline__ void wgmma_ss_n48_ta(float (&d)[24], uint32_t da, uint32_t db, int scale_d) {
  asm volatile("{\n.reg .pred p;\n.reg .b64 da, db;\nsetp.ne.b32 p, %26, 0;\nmov.b64 da, {%24, 0x40000040};\nmov.b64 db, {%25, 0x40000040};\n"
    "wgmma.mma_async.sync.aligned.m64n48k16.f32.bf16.bf16 {%0, %1, %2, %3, %4, %5, %6, %7, %8, %9, %10, %11, %12, %13, %14, %15, %16, %17, %18, %19, %20, %21, %22, %23}, da, db, p, 1, 1, 1, 0;\n}\n"
    : "+f"(d[0]), "+f"(d[1]), "+f"(d[2]), "+f"(d[3]), "+f"(d[4]), "+f"(d[5]), "+f"(d[6]), "+f"(d[7]), "+f"(d[8]), "+f"(d[9]), "+f"(d[10]), "+f"(d[11]), "+f"(d[12]), "+f"(d[13]), "+f"(d[14]), "+f"(d[15]), "+f"(d[16]), "+f"(d[17]), "+f"(d[18]), "+f"(d[19]), "+f"(d[20]), "+f"(d[21]), "+f"(d[22]), "+f"(d[23])
    : "r"(da), "r"(db), "r"(scale_d));
}

__device__ __forceinline__ void wgmma_ss_n192_ta(float (&d)[48], float (&e)[48], uint32_t da, uint32_t db, int scale_d) {
  asm volatile("{\n.reg .pred p;\n.reg .b64 da, db;\nsetp.ne.b32 p, %98, 0;\nmov.b64 da, {%96, 0x40000040};\nmov.b64 db, {%97, 0x40000040};\n"
    "wgmma.mma_async.sync.aligned.m64n192k16.f32.bf16.bf16 {%0, %1, %2, %3, %4, %5, %6, %7, %8, %9, %10, %11, %12, %13, %14, %15, %16, %17, %18, %19, %20, %21, %22, %23, %24, %25, %26, %27, %28, %29, %30, %31, %32, %33, %34, %35, %36, %37, %38, %39, %40, %41, %42, %43, %44, %45, %46, %47, %48, %49, %50, %51, %52, %53, %54, %55, %56, %57, %58, %59, %60, %61, %62, %63, %64, %65, %66, %67, %68, %69, %70, %71, %72, %73, %74, %75, %76, %77, %78, %79, %80, %81, %82, %83, %84, %85, %86, %87, %88, %89, %90, %91, %92, %93, %94, %95}, da, db, p, 1, 1, 1, 0;\n}\n"
    : "+f"(d[0]), "+f"(d[1]), "+f"(d[2]), "+f"(d[3]), "+f"(d[4]), "+f"(d[5]), "+f"(d[6]), "+f"(d[7]), "+f"(d[8]), "+f"(d[9]), "+f"(d[10]), "+f"(d[11]), "+f"(d[12]), "+f"(d[13]), "+f"(d[14]), "+f"(d[15]), "+f"(d[16]), "+f"(d[17]), "+f"(d[18]), "+f"(d[19]), "+f"(d[20]), "+f"(d[21]), "+f"(d[22]), "+f"(d[23]), "+f"(d[24]), "+f"(d[25]), "+f"(d[26]), "+f"(d[27]), "+f"(d[28]), "+f"(d[29]), "+f"(d[30]), "+f"(d[31]), "+f"(d[32]), "+f"(d[33]), "+f"(d[34]), "+f"(d[35]), "+f"(d[36]), "+f"(d[37]), "+f"(d[38]), "+f"(d[39]), "+f"(d[40]), "+f"(d[41]), "+f"(d[42]), "+f"(d[43]), "+f"(d[44]), "+f"(d[45]), "+f"(d[46]), "+f"(d[47]), "+f"(e[0]), "+f"(e[1]), "+f"(e[2]), "+f"(e[3]), "+f"(e[4]), "+f"(e[5]), "+f"(e[6]), "+f"(e[7]), "+f"(e[8]), "+f"(e[9]), "+f"(e[10]), "+f"(e[11]), "+f"(e[12]), "+f"(e[13]), "+f"(e[14]), "+f"(e[15]), "+f"(e[16]), "+f"(e[17]), "+f"(e[18]), "+f"(e[19]), "+f"(e[20]), "+f"(e[21]), "+f"(e[22]), "+f"(e[23]), "+f"(e[24]), "+f"(e[25]), "+f"(e[26]), "+f"(e[27]), "+f"(e[28]), "+f"(e[29]), "+f"(e[30]), "+f"(e[31]), "+f"(e[32]), "+f"(e[33]), "+f"(e[34]), "+f"(e[35]), "+f"(e[36]), "+f"(e[37]), "+f"(e[38]), "+f"(e[39]), "+f"(e[40]), "+f"(e[41]), "+f"(e[42]), "+f"(e[43]), "+f"(e[44]), "+f"(e[45]), "+f"(e[46]), "+f"(e[47])
    : "r"(da), "r"(db), "r"(scale_d));
}

template <int NT = 12>
__device__ __forceinline__ void store_acc_T(const float* acc, uint32_t tile_addr_plus_fragoff) {
#pragma unroll
  for (int jj = 0; jj < NT; jj += 2) {
    stsm_x4_t(tile_addr_plus_fragoff + jj * 1024,
              pack_bf16(acc[4 * jj + 0], acc[4 * jj + 1]), pack_bf16(acc[4 * jj + 2], acc[4 * jj + 3]),
              pack_bf16(acc[4 * jj + 4], acc[4 * jj + 5]), pack_bf16(acc[4 * jj + 6], acc[4 * jj + 7]));
  }
}

template <bool FIRST>
__device__ __forceinline__ void qproj_tile(int j, uint32_t sb, int g, int lane, uint32_t frag_off, uint32_t (&wr)[NWQ][4],
                                           int& slot, uint32_t& xph) {
  float acc[48];
  const uint32_t bars = sb + OFF_BAR;
  const uint32_t xlo = opaque(desc_lo(sb + OFF_X, 16));
  int prev = 0, prev2 = 0;
  if (j == 4 && (threadIdx.x & 127) == 0) PROF(128 + g * 16 + 0);
  if (!(DBG_NOX && j >= 1)) mbar_wait(bars + (B_XFULL + slot) * 8, xph);
  if (!FIRST) named_bar(4 + g, 256);
  if (j == 4 && (threadIdx.x & 127) == 0) PROF(128 + g * 16 + 1);
#pragma unroll
  for (int ks = 0; ks < 8; ++ks) {
    if (FIRST) {
      mbar_wait(bars + (B_WFULL + g * 8 + ks) * 8, 0);
      if ((threadIdx.x & 127) == 0) PROF(208 + g * 8 + ks);
#pragma unroll
      for (int kk = 0; kk < 4; ++kk)
        if (ks * 4 + kk < NWQ) ldsm_x4_t(wr[ks * 4 + kk], sb + (g ? w_stage(1, ks) : w_stage(0, ks)) + kk * 2048 + frag_off);
      if (ks == 2) { __syncwarp(); if (lane == 0) mbar_arrive(bars + (B_WDONE + 1) * 8); }
      if (ks == 7) {
        __syncwarp();
        if (lane == 0) mbar_arrive(bars + B_WDONE * 8);
        if (g == 1 && lane < 2) mbar_arrive_cta(bars + B_WFREE * 8, lane);
      }
    }
    const uint32_t xs = xlo + slot * (X_SLOT >> 4);
    wg_fence();
#pragma unroll
    for (int kk = 0; kk < 4; ++kk) {
      if (ks == 0 && kk == 0)
        wgmma_rs_n96_z(acc, wr[0][0], wr[0][1], wr[0][2], wr[0][3], xs);
      else if (ks * 4 + kk < NWQ)
        wgmma_rs_n96(acc, wr[ks * 4 + kk][0], wr[ks * 4 + kk][1], wr[ks * 4 + kk][2], wr[ks * 4 + kk][3], xs + kk * 2, 1);
      else
        wgmma_ss_n96_ta(acc, xlo + ((OFF_WP - OFF_X + (kk - 2) * 2048) >> 4) + g * 256, xs + kk * 2, 1);
    }
    wg_commit();
    if (ks == PP_HAND && !(FIRST && g == 0) && !(j == 7 && g == 1)) named_arrive(4 + (g ^ 1), 256);
    const int cur = slot;
    if (++slot == X_NS) { slot = 0; xph ^= 1; }
    if (ks < 7 && !(DBG_NOX && j >= 1)) mbar_wait(bars + (B_XFULL + slot) * 8, xph);
    if (ks > 0) {
      wg_wait<1>();
      if (lane < 2) mbar_arrive_cta(bars + (B_XEMPTY + prev) * 8, lane);
    }
    prev = cur;
  }
  wg_wait<0>();
  if (lane < 2) mbar_arrive_cta(bars + (B_XEMPTY + prev) * 8, lane);
  if ((threadIdx.x & 127) == 0) PROF(8 + g * 8 + j);
  if (j == 4 && (threadIdx.x & 127) == 0) PROF(128 + g * 16 + 2);
  const int buf = j & 1;
  if (FIRST) mbar_wait(bars + B_WDONE * 8, 0);
  if (j >= 2) mbar_wait(bars + (B_QEMPTY + buf) * 8, ((j >> 1) - 1) & 1);
  if (j == 4 && (threadIdx.x & 127) == 0) PROF(128 + g * 16 + 3);
  store_acc_T<DBG_NOEPI ? 2 : 12>(acc, sb + OFF_QO + buf * QO_BUF + g * 12288 + frag_off);
  fence_async_smem();
  __syncwarp();
  if (lane == 0) mbar_arrive(bars + (B_QFULL + buf) * 8);
  if (j == 4 && (threadIdx.x & 127) == 0) PROF(128 + g * 16 + 4);
}

__device__ __forceinline__ void pv_tile(int j, uint32_t sb, int g, int lane, uint32_t frag_off) {
  float o0[24], o1[24];
  const uint32_t bars = sb + OFF_BAR;
  const uint32_t vlo = desc_lo(sb + OFF_V + g * 6144, 16), plo = desc_lo(sb + OFF_P, 16);
  mbar_wait(bars + B_VFULL * 8, j & 1);
  if (j == 3 && (threadIdx.x & 127) == 0) PROF(128 + g * 16 + 5);
  if (!DBG_NOP) mbar_wait(bars + B_PFULL * 8, j & 1);
  if (j == 3 && (threadIdx.x & 127) == 0) PROF(128 + g * 16 + 6);
  wg_fence();
#pragma unroll
  for (int kk = 0; kk < 3; ++kk) {
    if (kk == 0) {
      wgmma_ss_n48_ta_z(o0, vlo, plo);
      wgmma_ss_n48_ta_z(o1, vlo + 768, plo + 384);
    } else {
      wgmma_ss_n48_ta(o0, vlo + kk * 128, plo + kk * 2, 1);
      wgmma_ss_n48_ta(o1, vlo + 768 + kk * 128, plo + 384 + kk * 2, 1);
    }
  }
  wg_commit();
  wg_wait<0>();
  if (j == 3 && (threadIdx.x & 127) == 0) PROF(128 + g * 16 + 7);
  if (lane == 0) mbar_arrive(bars + B_VEMPTY * 8);
  const int buf = j & 1;
  store_acc_T<DBG_NOEPI ? 2 : 6>(o0, sb + OFF_QO + buf * QO_BUF + g * 12288 + frag_off);
  store_acc_T<DBG_NOEPI ? 2 : 6>(o1, sb + OFF_QO + buf * QO_BUF + g * 12288 + frag_off + 6144);
  fence_async_smem();
  __syncwarp();
  if (lane == 0) mbar_arrive(bars + (B_OFULL + buf) * 8);
  if ((threadIdx.x & 127) == 0) PROF(24 + g * 8 + j);
  if (j == 3 && (threadIdx.x & 127) == 0) PROF(128 + g * 16 + 8);
}

__device__ __forceinline__ void softmax_exp(float (&s)[24], float& i0, float& i1) {
  const float sc = 0.08838834764831845f * 1.4426950408889634f;
  float m0 = fmaxf(s[0], s[1]), m1 = fmaxf(s[2], s[3]);
#pragma unroll
  for (int i = 1; i < 6; ++i) { m0 = fmaxf(m0, fmaxf(s[4 * i], s[4 * i + 1])); m1 = fmaxf(m1, fmaxf(s[4 * i + 2], s[4 * i + 3])); }
  m0 = fmaxf(m0, __shfl_xor_sync(0xffffffffu, m0, 1)); m1 = fmaxf(m1, __shfl_xor_sync(0xffffffffu, m1, 1));
  m0 = fmaxf(m0, __shfl_xor_sync(0xffffffffu, m0, 2)); m1 = fmaxf(m1, __shfl_xor_sync(0xffffffffu, m1, 2));
  const float b0 = -m0 * sc, b1 = -m1 * sc;
  float l0 = 0.f, l1 = 0.f;
#pragma unroll
  for (int i = 0; i < 6; ++i) {
    s[4 * i] = ex2(fmaf(s[4 * i], sc, b0)); s[4 * i + 1] = ex2(fmaf(s[4 * i + 1], sc, b0));
    s[4 * i + 2] = ex2(fmaf(s[4 * i + 2], sc, b1)); s[4 * i + 3] = ex2(fmaf(s[4 * i + 3], sc, b1));
    l0 += s[4 * i] + s[4 * i + 1]; l1 += s[4 * i + 2] + s[4 * i + 3];
  }
  l0 += __shfl_xor_sync(0xffffffffu, l0, 1); l1 += __shfl_xor_sync(0xffffffffu, l1, 1);
  l0 += __shfl_xor_sync(0xffffffffu, l0, 2); l1 += __shfl_xor_sync(0xffffffffu, l1, 2);
  i0 = __fdividef(1.f, l0); i1 = __fdividef(1.f, l1);
}

__device__ __forceinline__ void issue_scores(float (&s)[24], uint32_t qlo, uint32_t klo) {
#pragma unroll
  for (int kk = 0; kk < 8; ++kk) {
    if (kk == 0) wgmma_ss_n48_z(s, qlo, klo);
    else wgmma_ss_n48(s, qlo + (kk >> 2) * 768 + (kk & 3) * 2, klo + (kk >> 2) * 384 + (kk & 3) * 2, 1);
  }
}
__device__ __forceinline__ void store_p(const float (&s)[24], float i0, float i1, uint32_t a, int lane) {
#pragma unroll
  for (int jj = 0; jj < 6; jj += 2) {
    const int oct = jj + (lane >> 4);
    stsm_x4(a + ((oct ^ (lane & 7)) << 4), pack_bf16(s[4 * jj] * i0, s[4 * jj + 1] * i0), pack_bf16(s[4 * jj + 2] * i1, s[4 * jj + 3] * i1),
            pack_bf16(s[4 * jj + 4] * i0, s[4 * jj + 5] * i0), pack_bf16(s[4 * jj + 6] * i1, s[4 * jj + 7] * i1));
  }
}

__device__ __forceinline__ void load_w(uint32_t sb, const CUtensorMap* m, int head, int ks) {
  const uint64_t pol = policy_evict_first();
#pragma unroll
  for (int g = 0; g < 2; ++g) {
    const uint32_t wb = sb + OFF_BAR + (B_WFULL + g * 8 + ks) * 8;
    const uint32_t d = sb + (ks < 3 ? OFF_K + (ks * 2 + g) * 8192 : (ks < 6 ? OFF_QO + ((ks - 3) * 2 + g) * 8192 : (g ? 98304 : OFF_P) + (ks - 6) * 8192));
    mbar_expect_tx(wb, 8192);
    tma_ld_hint(d, m, head * 128 + g * 64, ks * 64, wb, pol);
    tma_ld_hint(ks == 7 ? sb + OFF_WP + g * 4096 : d + 4096, m, head * 128 + g * 64, ks * 64 + 32, wb, pol);
  }
}

__global__ void __cluster_dims__(2, 1, 1) __launch_bounds__(NTHREADS, 1)
fused_kernel(const __grid_constant__ Params P) {
  extern __shared__ uint8_t smem_raw[];
  const uint32_t sb = (smem_u32(smem_raw) + 1023u) & ~1023u;
  const uint32_t bars = sb + OFF_BAR;
  const int tid = threadIdx.x, warp = tid >> 5, lane = tid & 31;
  const int rank = blockIdx.x & 1;
  const int cid = blockIdx.x >> 1;
  const int br = cid >> 5;
  const int c5 = cid & 31;
  const int pj = c5 >> 1, half = c5 & 1;
  const int head = pj * 2 + rank;
  const int r0 = pj & 3;
  const int T = c5 >> 2, kh = (c5 >> 1) & 1, cs = (c5 & 1) * 2 + rank;

  if (tid == 384) {
    PROF(0);
    asm volatile("prefetch.tensormap [%0];" :: "l"(&P.wq[br]) : "memory");
    for (int i = 0; i < 16; ++i) mbar_init(bars + (B_WFULL + i) * 8, 1);
    asm volatile("fence.mbarrier_init.release.cluster;" ::: "memory");
    fence_async_smem();
  } else if (tid == 0) {
    for (int i = 0; i < X_NS; ++i) { mbar_init(bars + (B_XFULL + i) * 8, 1); mbar_init(bars + (B_XEMPTY + i) * 8, 16); }
    for (int i = 0; i < 2; ++i) { mbar_init(bars + (B_QFULL + i) * 8, 8); mbar_init(bars + (B_QEMPTY + i) * 8, 1); }
    for (int i = 0; i < 2; ++i) { mbar_init(bars + (B_KFULL + i) * 8, 1); mbar_init(bars + (B_VFULL + i) * 8, 1); mbar_init(bars + (B_WDONE + i) * 8, 8); }
    asm volatile("fence.mbarrier_init.release.cluster;" ::: "memory");
  } else if (tid == 32) {
    for (int i = 0; i < P2_NST; ++i) { mbar_init(bars + (B_P2FULL + i) * 8, 1); mbar_init(bars + (B_P2EMPTY + i) * 8, 16); }
    mbar_init(bars + B_KEMPTY * 8, 4);
    mbar_init(bars + B_WFREE * 8, 8);
    mbar_init(bars + B_VEMPTY * 8, 8);
    mbar_init(bars + B_PFULL * 8, 3);
    for (int i = 0; i < 2; ++i) { mbar_init(bars + (B_OFULL + i) * 8, 8); mbar_init(bars + (B_OST + i) * 8, 2); }
    asm volatile("fence.mbarrier_init.release.cluster;" ::: "memory");
  } else if (tid == 64) {
    for (int i = 0; i < 20; ++i) mbar_init(bars + (B_HREADY + i) * 8, 1);
    mbar_init(bars + B_KDONE * 8, 4);
    mbar_init(bars + B_VDONE * 8, 16);
    asm volatile("fence.mbarrier_init.release.cluster;" ::: "memory");
  } else if (tid == 96) {
    l2_prefetch((const char*)P.xp[br] + (size_t)(blockIdx.x & 63) * 24576, 24576);
    asm volatile("prefetch.tensormap [%0];" :: "l"(&P.x[br]) : "memory");
    asm volatile("prefetch.tensormap [%0];" :: "l"(&P.k[br]) : "memory");
    asm volatile("prefetch.tensormap [%0];" :: "l"(&P.v[br]) : "memory");
    asm volatile("prefetch.tensormap [%0];" :: "l"(&P.o) : "memory");
  }
  __syncwarp();
  asm volatile("barrier.cluster.arrive.relaxed.aligned;" ::: "memory");
  if (tid == 384) {
    load_w(sb, &P.wq[br], head, 0);
  }
  __syncwarp();
  asm volatile("barrier.cluster.wait.aligned;" ::: "memory");
  if (tid == 0) PROF(1);

  if (warp < 8) {
    asm volatile("setmaxnreg.inc.sync.aligned.u32 200;");
    const int g = warp >> 2;
    const uint32_t frag_off = ((lane >> 4) * 8 + (lane & 7)) * 128 + (((2 * (warp & 3) + ((lane >> 3) & 1)) ^ (lane & 7)) << 4);
    {
      uint32_t wr[NWQ][4];
      int slot = 0; uint32_t xph = 0;
      qproj_tile<true>(0, sb, g, lane, frag_off, wr, slot, xph);
#pragma unroll 1
      for (int j = 1; j < 8; ++j) {
        qproj_tile<false>(j, sb, g, lane, frag_off, wr, slot, xph);
        pv_tile(j - 1, sb, g, lane, frag_off);
      }
    }
    {
      const int bid = fresh_ctaid(), tid = fresh_tid();
      const int br = bid >> 6, T = (bid >> 3) & 7, kh = (bid >> 2) & 1, cs = bid & 3;
      float accK[48], accS[48];
#pragma unroll
      for (int i = 0; i < 48; ++i) { accK[i] = 0.f; accS[i] = 0.f; }
      const uint32_t tag = (ld_relaxed(&g_done) / NCTA + 1u) & 3u;
      if (PV7_AT < 0) pv_tile(7, sb, g, lane, frag_off);
      int st = 0; uint32_t ph = 0; int prev = 0;
      mbar_wait(bars + B_P2FULL * 8, 0);
#pragma unroll 1
      for (int it = 0; it < P2_FULL; ++it) {
        if (tid == 0) PROF(72 + it);
        const uint32_t alo = desc_lo(sb + p2_a(st, g), 16), blo = desc_lo(sb + p2_b(st), 16);
        wg_fence();
#pragma unroll
        for (int kk = 0; kk < 4; ++kk) wgmma_ss_n192_ta(accK, accS, alo + kk * 128, blo + kk * 2, 1);
        wg_commit();
        const int cur = st;
        if (++st == P2_NST) { st = 0; ph ^= 1; }
        if (it == PV7_AT) {
          wg_wait<0>();
          if (lane < 2) { if (it > 0) mbar_arrive_cta(bars + (B_P2EMPTY + prev) * 8, lane); }
          pv_tile(7, sb, g, lane, frag_off);
          mbar_wait(bars + (B_P2FULL + st) * 8, ph);
        } else {
          mbar_wait(bars + (B_P2FULL + st) * 8, ph);
          if (it > 0) {
            wg_wait<1>();
            if (lane < 2) mbar_arrive_cta(bars + (B_P2EMPTY + prev) * 8, lane);
          }
        }
        prev = cur;
      }
      wg_wait<0>();
      if (lane < 2) mbar_arrive_cta(bars + (B_P2EMPTY + prev) * 8, lane);
      uint4* dst = g_part + (size_t)bid * 12 * 256 + tid;
#pragma unroll
      for (int it = P2_FULL; it < P2_ITS; ++it) {
        const uint32_t alo = desc_lo(sb + p2_a(st, g), 16), blo = desc_lo(sb + p2_b(st), 16);
        wg_fence();
#pragma unroll
        for (int kk = 0; kk < 4; ++kk) wgmma_ss_n96_ta(accK, alo + kk * 128, blo + kk * 2, 1);
        wg_commit();
        const int cur = st;
        if (++st == P2_NST) { st = 0; ph ^= 1; }
        if (it - P2_FULL < 12 / SEND_PER) {
#pragma unroll
          for (int i = (it - P2_FULL) * SEND_PER; i < (it - P2_FULL + 1) * SEND_PER; ++i)
            asm volatile("st.global.v4.b32 [%0], {%1, %2, %3, %4};" :: "l"(dst + i * 256), "r"((__float_as_uint(accS[4 * i]) & ~3u) | tag),
                         "r"((__float_as_uint(accS[4 * i + 1]) & ~3u) | tag), "r"((__float_as_uint(accS[4 * i + 2]) & ~3u) | tag),
                         "r"((__float_as_uint(accS[4 * i + 3]) & ~3u) | tag) : "memory");
          if (tid == 0) PROF(5);
        }
        if (tid == 0) PROF(240 + it - P2_FULL);
        if (it < P2_ITS - 1) mbar_wait(bars + (B_P2FULL + st) * 8, ph);
        if (it > P2_FULL) {
          wg_wait<1>();
          if (it <= P2_ITS - 5 && lane < 2) mbar_arrive_cta(bars + (B_P2EMPTY + prev) * 8, lane);
        }
        prev = cur;
      }
      if (tid == 0) PROF(6);
      const uint4* src = g_part + (size_t)(bid ^ 4) * 12 * 256 + tid;
      {
        uint32_t spins = 0;
        while ((ld_relaxed(&src[11 * 256].w) & 3u) != tag) { __nanosleep(40); if (++spins > (1u << 22)) __trap(); }
      }
      {
        uint4 v[12];
        uint32_t spins = 0;
        bool ok;
        do {
#pragma unroll
          for (int i = 0; i < 12; ++i) {
            asm volatile("ld.relaxed.gpu.global.v4.b32 {%0, %1, %2, %3}, [%4];" : "=r"(v[i].x), "=r"(v[i].y), "=r"(v[i].z), "=r"(v[i].w) : "l"(src + i * 256) : "memory");
          }
          uint32_t bad = 0;
#pragma unroll
          for (int i = 0; i < 12; ++i) bad |= (v[i].x ^ tag) | (v[i].y ^ tag) | (v[i].z ^ tag) | (v[i].w ^ tag);
          ok = (bad & 3u) == 0;
          if (++spins > (1u << 22)) __trap();
        } while (!ok);
        wg_wait<0>();
        if (tid == 0) PROF(2);
#pragma unroll
        for (int i = 0; i < 12; ++i) {
          accK[4 * i] += __uint_as_float(v[i].x & ~3u); accK[4 * i + 1] += __uint_as_float(v[i].y & ~3u);
          accK[4 * i + 2] += __uint_as_float(v[i].z & ~3u); accK[4 * i + 3] += __uint_as_float(v[i].w & ~3u);
        }
      }
      if (tid == 0) PROF(3);
      named_bar(1, 256);
      store_acc_T(accK, sb + g * 12288 + frag_off);
      fence_async_smem();
      named_bar(2 + g, 128);
      if ((tid & 127) == 0) {
        tma_st(&P.out_st, br * 512 + cs * 128 + g * 64, T * 192 + kh * 96, sb + g * 12288);
        bulk_commit();
        bulk_wait_read<0>();
        if (tid == 0) {
          PROF(4);
          atomicAdd(&g_done, 1u);
        }
      }
    }
  } else if (warp < 12) {
    asm volatile("setmaxnreg.dec.sync.aligned.u32 88;");
    const int w = warp - 8;
    const uint32_t pa = sb + OFF_P + (16 * w + ((lane >> 3) & 1) * 8 + (lane & 7)) * 128;
    const uint32_t klo = desc_lo(sb + OFF_K, 16);
#pragma unroll 1
    for (int j = 0; j < 8; ++j) {
      const int buf = j & 1;
      const uint32_t qlo = desc_lo(sb + OFF_QO + buf * QO_BUF, 16);
      float sa[24], sb2[24], i0, i1;
      mbar_wait(bars + (B_QFULL + buf) * 8, (j >> 1) & 1);
      mbar_wait(bars + (B_KFULL + 0) * 8, j & 1);
      if (tid == 256) PROF(56 + j);
      wg_fence();
      if (DBG_NOS) { wgmma_ss_n48_z(sa, qlo, klo); wgmma_ss_n48_z(sb2, qlo, klo); } else {
      issue_scores(sa, qlo, klo);
      issue_scores(sb2, qlo + 384, klo + 768); }
      wg_commit();
      wg_wait<0>();
      if (lane == 0) mbar_arrive(bars + (j == 7 ? B_KDONE : B_KEMPTY) * 8);
      if (tid == 256) PROF(104 + j);
      float i2, i3;
      softmax_exp(sa, i0, i1);
      softmax_exp(sb2, i2, i3);
      if (j > 0) mbar_wait(bars + B_VEMPTY * 8, (j - 1) & 1);
      if (w < 3) {
        store_p(sa, i0, i1, pa, lane);
        store_p(sb2, i2, i3, pa + 6144, lane);
        fence_async_smem();
        __syncwarp();
        if (lane == 0) mbar_arrive(bars + B_PFULL * 8);
      }
      if (tid == 256) PROF(40 + j);
    }
  } else {
    asm volatile("setmaxnreg.dec.sync.aligned.u32 24;");
    auto tile_of = [&](int j) { return half * 8 + ((((r0 + (j >> 1)) & 3) << 1) | (j & 1)); };
    if (tid == 416) {
      uint64_t pol;
      asm volatile("createpolicy.fractional.L2::evict_first.b64 %0, 1.0;" : "=l"(pol));
      auto prefetch_kv = [&](int n) {
        const size_t off = (size_t)((tile_of(n >> 1) * 2 + (n & 1)) * 32 + head) * 6144;
        l2_prefetch_hint(P.kp[br] + off, 12288, pol);
        l2_prefetch_hint(P.vp[br] + off, 12288, pol);
      };
      if (PF_START >= 0) mbar_wait(bars + (B_WFULL + (PF_START >= 0 ? PF_START : 0)) * 8, 0);
      for (int n = 2; n < PF_DIST; ++n) prefetch_kv(n);
      for (int n = PF_E0; n < PF_E1; ++n) prefetch_kv(n);
      mbar_wait(bars + (B_WDONE + 1) * 8, 0);
      int kj = 0, vj = 0;
      uint32_t spins = 0;
      while (kj < 8 || vj < 8) {
        if (kj < 8 && (kj == 0 || mbar_test(bars + B_KEMPTY * 8, (kj - 1) & 1))) {
          for (int sub = 0; sub < 2; ++sub) {
            const int row = DBG_KVSAME ? (sub * 32 + head) * 48 : ((tile_of(kj) * 2 + sub) * 32 + head) * 48;
            const uint32_t kbar = bars + B_KFULL * 8, kd = sb + OFF_K + sub * 12288;
            if (sub == 0) mbar_expect_tx(kbar, 24576);
            tma_ld_hint(kd, &P.k[br], 0, row, kbar, pol);
            tma_ld_hint(kd + 6144, &P.k[br], 64, row, kbar, pol);
          }
          for (int sub = 0; sub < 2; ++sub) {
            const int pn = 2 * kj + sub - 2 + PF_DIST;
            if (PF_DIST > 0 && kj >= 1 && pn < 16) prefetch_kv(pn);
          }
          if (kj == PF_LAST) { prefetch_kv(14); prefetch_kv(15); }
          ++kj;
        }
        if (vj < 8 && (vj == 0 || mbar_test(bars + B_VEMPTY * 8, (vj - 1) & 1))) {
          for (int sub = 0; sub < 2; ++sub) {
            const int row = DBG_KVSAME ? (sub * 32 + head) * 48 : ((tile_of(vj) * 2 + sub) * 32 + head) * 48;
            const uint32_t vbar = bars + B_VFULL * 8, vd = sb + OFF_V + sub * 12288;
            if (sub == 0) mbar_expect_tx(vbar, 24576);
            tma_ld_hint(vd, &P.v[br], 0, row, vbar, pol);
            tma_ld_hint(vd + 6144, &P.v[br], 64, row, vbar, pol);
          }
          ++vj;
        }
        __nanosleep(20);
        if (++spins > (1u << 24)) __trap();
      }
    } else if (tid == 448) {
      const unsigned epoch = ld_relaxed(&g_done) / NCTA + 1u;
      for (int j = 0; j < 8; ++j) {
        const int buf = j & 1;
        mbar_wait(bars + (B_OFULL + buf) * 8, (j >> 1) & 1);
        const int t = tile_of(j);
        const uint32_t qb = sb + OFF_QO + buf * QO_BUF;
        tma_st(&P.o, head * 128, br * 1536 + t * 96, qb);
        tma_st(&P.o, head * 128 + 64, br * 1536 + t * 96, qb + 12288);
        bulk_commit();
        bulk_wait_read<0>();
        mbar_arrive(bars + (B_QEMPTY + buf) * 8);
        if (j >= 6) { mbar_arrive_cta(bars + (B_OST + j - 6) * 8, 0); mbar_arrive_cta(bars + (B_OST + j - 6) * 8, 1); }
        bulk_wait<0>();
        asm volatile("fence.proxy.async.global;" ::: "memory");
        st_release(&g_oflag[(br * 16 + t) * 32 + head], epoch);
      }
    } else if (warp == 15) {
      const unsigned epoch = ld_relaxed(&g_done) / NCTA + 1u;
      const int idx = lane < 16 ? lane : 14 + (lane & 1);
      const int khl = lane < 16 ? kh : (kh ^ ((lane >> 1) & 1));
      const int q = (idx >> 2) & 3, hi = idx & 3;
      const int h2 = (khl * 8 + (hi >> 1) * 4 + k_order(q, T & 3)) * 2 + (hi & 1);
      const unsigned* fp = &g_oflag[(br * 16 + T * 2 + (lane < 16 ? rank : kh)) * 32 + h2];
      bool done = lane >= 20;
      uint32_t it = 0;
      while (!__all_sync(0xffffffffu, done)) {
        if (!done && ld_acquire(fp) == epoch) { mbar_arrive(bars + (B_HREADY + lane) * 8); done = true; }
        __nanosleep(200);
        if (++it > (1u << 22)) __trap();
      }
    } else if (tid == 384) {
      int slot = 0; uint32_t ph = 1;
      for (int j = 0; j < (DBG_NOX ? 1 : 8); ++j) {
        const int xrow = tile_of(j) * 96;
        for (int ks = 0; ks < 8; ++ks) {
          if (j == 1 && ks == 0) mbar_wait(bars + B_WFREE * 8, 0);
          mbar_wait(bars + (B_XEMPTY + slot) * 8, ph);
          const uint32_t xb = bars + (B_XFULL + slot) * 8;
          if (!(DBG_NOX && j >= 1)) mbar_expect_tx(xb, X_SLOT);
          if (j == 4 || j == 5) PROF(192 + (j - 4) * 8 + ks);
          if ((ks & 1) == rank && !(DBG_NOX && j >= 1)) tma_ld_mc(sb + OFF_X + slot * X_SLOT, &P.x[br], ks * 64, xrow, xb);
          if (++slot == X_NS) { slot = 0; ph ^= 1; }
          if (j == 0 && ks < 7) load_w(sb, &P.wq[br], head, ks + 1);
        }
        if (WO_PF_ON && j >= WO_PF && j < WO_PF + 4)
          l2_prefetch((const char*)P.wop[br] + (size_t)(blockIdx.x & 63) * 65536 + (j - WO_PF) * 16384, 16384);
        if (j == 6) {
          asm volatile("prefetch.tensormap [%0];" :: "l"(&P.wo[br]) : "memory");
          asm volatile("prefetch.tensormap [%0];" :: "l"(&P.out_st) : "memory");
        }
      }
      const int Tq = T & 3;
      const uint64_t pol2 = policy_evict_first();
      const int orow = br * 1536 + T * 192 + rank * 96;
      const uint32_t odst = (rank == kh) ? 0 : 12288;
      const uint32_t xph = ph;
      int st = 0; ph = 0;
      for (int it = 0; it < P2_ITS; ++it) {
        const bool tail = it >= P2_FULL;
        const int sl = tail ? P2_FULL + ((it - P2_FULL) >> 1) : it;
        const int khl = tail ? (kh ^ (it & 1)) : kh;
        const int q = sl >> 3, hi = (sl >> 1) & 3;
        const int h2 = (khl * 8 + (hi >> 1) * 4 + k_order(q, Tq)) * 2 + (hi & 1);
        const int k0 = h2 * 128 + (sl & 1) * 64;
        if (it < P2_NST) {
          if (it == 0) { for (int i = 1; i < 5; ++i) mbar_wait(bars + (B_XEMPTY + i) * 8, xph); }
          else if (it == 1) { for (int i = 5; i < 8; ++i) mbar_wait(bars + (B_XEMPTY + i) * 8, xph); }
          else if (it == 2) { mbar_wait(bars + B_KDONE * 8, 0); mbar_wait(bars + B_OST * 8, 0); }
          else if (it == 3) { mbar_wait(bars + (B_XEMPTY + 8) * 8, xph); mbar_wait(bars + B_XEMPTY * 8, xph ^ 1); }
          else mbar_wait(bars + (B_OST + 1) * 8, 0);
        } else {
          mbar_wait(bars + (B_P2EMPTY + st) * 8, ph ^ 1);
        }
        const uint32_t fb = bars + (B_P2FULL + st) * 8;
        mbar_expect_tx(fb, tail ? 28672 : 40960);
        if (EF_WO) { tma_ld_hint(sb + p2_a(st, 0), &P.wo[br], cs * 128, k0, fb, pol2); tma_ld_hint(sb + p2_a(st, 1), &P.wo[br], cs * 128 + 64, k0, fb, pol2); }
        else { tma_ld(sb + p2_a(st, 0), &P.wo[br], cs * 128, k0, fb); tma_ld(sb + p2_a(st, 1), &P.wo[br], cs * 128 + 64, k0, fb); }
        if (!tail) {
          if ((it & 1) == 0) { mbar_wait(bars + (B_HREADY + (it >> 1)) * 8, 0); asm volatile("fence.proxy.async.global;" ::: "memory"); }
          tma_ld_mc_hint(sb + p2_b(st) + odst, &P.o, k0, orow, fb, pol2);
        } else if ((it & 1) == rank) {
          mbar_wait(bars + (B_HREADY + 16 + (it & 1) * 2 + ((sl >> 1) & 1)) * 8, 0);
          asm volatile("fence.proxy.async.global;" ::: "memory");
          tma_ld_mc_hint(sb + p2_b(st), &P.o, k0, br * 1536 + T * 192 + kh * 96, fb, pol2);
        }
        if (++st == P2_NST) { st = 0; ph ^= 1; }
      }
    }
  }
}

typedef CUresult (*EncodeFn)(CUtensorMap*, CUtensorMapDataType, cuuint32_t, void*, const cuuint64_t*, const cuuint64_t*,
                             const cuuint32_t*, const cuuint32_t*, CUtensorMapInterleave, CUtensorMapSwizzle,
                             CUtensorMapL2promotion, CUtensorMapFloatOOBfill);

static void make_map(EncodeFn enc, CUtensorMap* m, const void* ptr, uint64_t cols, uint64_t rows, uint32_t box_rows) {
  cuuint64_t gdim[2] = {cols, rows};
  cuuint64_t gstr[1] = {cols * 2};
  cuuint32_t box[2] = {64, box_rows};
  cuuint32_t es[2] = {1, 1};
  enc(m, CU_TENSOR_MAP_DATA_TYPE_BFLOAT16, 2, const_cast<void*>(ptr), gdim, gstr, box, es, CU_TENSOR_MAP_INTERLEAVE_NONE,
      CU_TENSOR_MAP_SWIZZLE_128B, CU_TENSOR_MAP_L2_PROMOTION_L2_128B, CU_TENSOR_MAP_FLOAT_OOB_FILL_NONE);
}

}

extern "C" void kernel_launch(void* const* d_in, const int* in_sizes, int n_in, void* d_out, int out_size) {
  using namespace fk;
  (void)in_sizes; (void)n_in; (void)out_size;
  static EncodeFn enc = nullptr;
  static void* o_ptr = nullptr;
  if (!enc) {
    cudaDriverEntryPointQueryResult qr;
    cudaGetDriverEntryPoint("cuTensorMapEncodeTiled", (void**)&enc, cudaEnableDefault, &qr);
    cudaGetSymbolAddress(&o_ptr, g_O);
    cudaFuncSetAttribute(fused_kernel, cudaFuncAttributeMaxDynamicSharedMemorySize, SMEM_BYTES);
  }
  Params P;
  for (int b = 0; b < 2; ++b) {
    make_map(enc, &P.x[b], d_in[5 * b + 0], 512, 1536, 96);
    make_map(enc, &P.k[b], d_in[5 * b + 1], 128, 32 * 32 * 48, 48);
    make_map(enc, &P.v[b], d_in[5 * b + 2], 128, 32 * 32 * 48, 48);
    make_map(enc, &P.wq[b], d_in[5 * b + 3], 4096, 512, 32);
    make_map(enc, &P.wo[b], d_in[5 * b + 4], 512, 4096, 64);
    P.kp[b] = (const __nv_bfloat16*)d_in[5 * b + 1];
    P.vp[b] = (const __nv_bfloat16*)d_in[5 * b + 2];
    P.wop[b] = (const __nv_bfloat16*)d_in[5 * b + 4];
    P.xp[b] = (const __nv_bfloat16*)d_in[5 * b + 0];
  }
  make_map(enc, &P.o, o_ptr, 4096, 3072, 96);
  make_map(enc, &P.out_st, d_out, 1024, 1536, 96);
  fused_kernel<<<NCTA, NTHREADS, SMEM_BYTES, cudaStreamPerThread>>>(P);
}
```

```cpp
#include <cuda_runtime.h>
#include <cuda_bf16.h>
#include <cuda.h>
#include <stdint.h>

namespace fk {

constexpr int NTHREADS = 512;
constexpr int NCTA = 128;

constexpr int X_SLOT   = 12288;
constexpr int X_NS     = 9;
constexpr int OFF_X    = 0;
constexpr int QO_BUF   = 24576;
constexpr int OFF_QO   = 118784;
constexpr int OFF_K    = 167936;
constexpr int OFF_V    = 192512;
constexpr int OFF_P    = 217088;
constexpr int OFF_WP   = 110592;
constexpr int P2_NST   = 5;
constexpr int P2_TAIL  = 4;
constexpr int P2_FULL  = 32 - P2_TAIL;
constexpr int P2_ITS   = 32 + P2_TAIL;
constexpr int OFF_BAR  = 229376;
constexpr int SMEM_BYTES = OFF_BAR + 768 + 1024;
constexpr int PP_HAND  = 3;
constexpr int PV7_AT   = 1;
constexpr int NWQ = 30;

__device__ __forceinline__ constexpr uint32_t w_stage(int g, int ks) {
  return ks < 3 ? OFF_K + (ks * 2 + g) * 8192 : (ks < 6 ? OFF_QO + ((ks - 3) * 2 + g) * 8192 : (g ? 98304 : OFF_P) + (ks - 6) * 8192);
}
__device__ __forceinline__ uint32_t p2_a(int st, int g) {
  return st == 0 ? 12288 + g * 8192 : st == 1 ? 53248 + g * 8192 : st == 2 ? OFF_K + g * 8192 : st == 3 ? (g ? OFF_K + 16384 : 0) : OFF_V + g * 8192;
}
__device__ __forceinline__ uint32_t p2_b(int st) {
  return st == 0 ? 28672 : st == 1 ? 69632 : st == 2 ? OFF_QO : st == 3 ? 94208 : OFF_QO + QO_BUF;
}

__device__ __forceinline__ int k_order(int q, int Tq) {
  return (Tq == 3 && q < 2) ? 1 - q : q;
}

constexpr int B_XFULL = 0, B_XEMPTY = 9, B_WFULL = 18, B_QFULL = 34, B_QEMPTY = 36, B_KFULL = 38, B_VFULL = 40,
              B_P2FULL = 42, B_P2EMPTY = 47, B_WDONE = 52, B_KEMPTY = 54, B_WFREE = 55, B_VEMPTY = 56, B_PFULL = 57, B_OFULL = 58,
              B_OST = 60, B_KDONE = 62, B_HREADY = 64;

struct __align__(64) Params {
  CUtensorMap x[2], wq[2], k[2], v[2], wo[2], o, out_st;
  const __nv_bfloat16* xp[2];
};

__device__ __nv_bfloat16 g_O[3072 * 4096];
__device__ uint4 g_part[NCTA * 12 * 256];
__device__ unsigned g_oflag[2 * 16 * 32];
__device__ unsigned g_done;

__device__ __forceinline__ uint32_t smem_u32(const void* p) { return (uint32_t)__cvta_generic_to_shared(p); }
__device__ __forceinline__ void mbar_init(uint32_t bar, int cnt) { asm volatile("mbarrier.init.shared::cta.b64 [%0], %1;" :: "r"(bar), "r"(cnt) : "memory"); }
__device__ __forceinline__ void mbar_expect_tx(uint32_t bar, uint32_t bytes) { asm volatile("mbarrier.arrive.expect_tx.shared::cta.b64 _, [%0], %1;" :: "r"(bar), "r"(bytes) : "memory"); }
__device__ __forceinline__ void mbar_arrive(uint32_t bar) { asm volatile("mbarrier.arrive.shared::cta.b64 _, [%0];" :: "r"(bar) : "memory"); }
__device__ __forceinline__ void mbar_arrive_cta(uint32_t bar, uint32_t cta) {
  asm volatile("{\n.reg .b32 r;\nmapa.shared::cluster.u32 r, %0, %1;\nmbarrier.arrive.shared::cluster.b64 _, [r];\n}\n" :: "r"(bar), "r"(cta) : "memory");
}
__device__ __forceinline__ uint32_t mbar_try(uint32_t bar, uint32_t parity) {
  uint32_t ok;
  asm volatile("{\n.reg .pred p;\nmbarrier.try_wait.parity.shared::cta.b64 p, [%1], %2;\nselp.u32 %0, 1, 0, p;\n}\n" : "=r"(ok) : "r"(bar), "r"(parity) : "memory");
  return ok;
}
__device__ __forceinline__ void mbar_wait(uint32_t bar, uint32_t parity) {
  if (mbar_try(bar, parity)) return;
  uint32_t it = 0;
  while (!mbar_try(bar, parity)) { if (++it > (1u << 22)) __trap(); }
}
__device__ __forceinline__ void tma_ld(uint32_t dst, const CUtensorMap* m, int c0, int c1, uint32_t bar) {
  asm volatile("cp.async.bulk.tensor.2d.shared::cluster.global.mbarrier::complete_tx::bytes [%0], [%1, {%3, %4}], [%2];"
               :: "r"(dst), "l"(m), "r"(bar), "r"(c0), "r"(c1) : "memory");
}
__device__ __forceinline__ void tma_ld_hint(uint32_t dst, const CUtensorMap* m, int c0, int c1, uint32_t bar, uint64_t pol) {
  asm volatile("cp.async.bulk.tensor.2d.shared::cluster.global.mbarrier::complete_tx::bytes.L2::cache_hint [%0], [%1, {%3, %4}], [%2], %5;"
               :: "r"(dst), "l"(m), "r"(bar), "r"(c0), "r"(c1), "l"(pol) : "memory");
}
__device__ __forceinline__ void tma_ld_mc(uint32_t dst, const CUtensorMap* m, int c0, int c1, uint32_t bar) {
  asm volatile("cp.async.bulk.tensor.2d.shared::cluster.global.mbarrier::complete_tx::bytes.multicast::cluster [%0], [%1, {%3, %4}], [%2], %5;"
               :: "r"(dst), "l"(m), "r"(bar), "r"(c0), "r"(c1), "h"((uint16_t)3) : "memory");
}
__device__ __forceinline__ void tma_ld_mc_hint(uint32_t dst, const CUtensorMap* m, int c0, int c1, uint32_t bar, uint64_t pol) {
  asm volatile("cp.async.bulk.tensor.2d.shared::cluster.global.mbarrier::complete_tx::bytes.multicast::cluster.L2::cache_hint [%0], [%1, {%3, %4}], [%2], %5, %6;"
               :: "r"(dst), "l"(m), "r"(bar), "r"(c0), "r"(c1), "h"((uint16_t)3), "l"(pol) : "memory");
}
__device__ __forceinline__ void tma_st(const CUtensorMap* m, int c0, int c1, uint32_t src) {
  asm volatile("cp.async.bulk.tensor.2d.global.shared::cta.bulk_group [%0, {%2, %3}], [%1];" :: "l"(m), "r"(src), "r"(c0), "r"(c1) : "memory");
}
__device__ __forceinline__ void bulk_commit() { asm volatile("cp.async.bulk.commit_group;" ::: "memory"); }
template <int N> __device__ __forceinline__ void bulk_wait_read() { asm volatile("cp.async.bulk.wait_group.read %0;" :: "n"(N) : "memory"); }
template <int N> __device__ __forceinline__ void bulk_wait() { asm volatile("cp.async.bulk.wait_group %0;" :: "n"(N) : "memory"); }
__device__ __forceinline__ void l2_prefetch(const void* p, uint32_t bytes) { asm volatile("cp.async.bulk.prefetch.L2.global [%0], %1;" :: "l"(p), "r"(bytes) : "memory"); }
__device__ __forceinline__ uint64_t policy_evict_first() { uint64_t pol; asm volatile("createpolicy.fractional.L2::evict_first.b64 %0, 1.0;" : "=l"(pol)); return pol; }
__device__ __forceinline__ void fence_async_smem() { asm volatile("fence.proxy.async.shared::cta;" ::: "memory"); }
__device__ __forceinline__ void wg_fence() { asm volatile("wgmma.fence.sync.aligned;" ::: "memory"); }
__device__ __forceinline__ void wg_commit() { asm volatile("wgmma.commit_group.sync.aligned;" ::: "memory"); }
template <int N> __device__ __forceinline__ void wg_wait() { asm volatile("wgmma.wait_group.sync.aligned %0;" :: "n"(N) : "memory"); }
__device__ __forceinline__ void named_arrive(int id, int n) { asm volatile("bar.arrive %0, %1;" :: "r"(id), "r"(n) : "memory"); }
__device__ __forceinline__ uint32_t mbar_test(uint32_t bar, uint32_t parity) {
  uint32_t ok;
  asm volatile("{\n.reg .pred p;\nmbarrier.test_wait.parity.shared::cta.b64 p, [%1], %2;\nselp.u32 %0, 1, 0, p;\n}\n" : "=r"(ok) : "r"(bar), "r"(parity) : "memory");
  return ok;
}
__device__ __forceinline__ void named_bar(int id, int n) { asm volatile("bar.sync %0, %1;" :: "r"(id), "r"(n) : "memory"); }
__device__ __forceinline__ uint32_t desc_lo(uint32_t addr, uint32_t lbo) { return ((addr & 0x3FFFF) >> 4) | ((lbo >> 4) << 16); }
__device__ __forceinline__ uint32_t opaque(uint32_t v) { asm volatile("mov.u32 %0, %0;" : "+r"(v)); return v; }
__device__ __forceinline__ uint32_t pack_bf16(float lo, float hi) {
  uint32_t r; asm("cvt.rn.bf16x2.f32 %0, %1, %2;" : "=r"(r) : "f"(hi), "f"(lo)); return r;
}
__device__ __forceinline__ void ldsm_x4_t(uint32_t (&r)[4], uint32_t addr) {
  asm volatile("ldmatrix.sync.aligned.m8n8.x4.trans.shared.b16 {%0,%1,%2,%3}, [%4];" : "=r"(r[0]), "=r"(r[1]), "=r"(r[2]), "=r"(r[3]) : "r"(addr) : "memory");
}
__device__ __forceinline__ void stsm_x4_t(uint32_t addr, uint32_t a, uint32_t b, uint32_t c, uint32_t d) {
  asm volatile("stmatrix.sync.aligned.m8n8.x4.trans.shared.b16 [%0], {%1,%2,%3,%4};" :: "r"(addr), "r"(a), "r"(b), "r"(c), "r"(d) : "memory");
}
__device__ __forceinline__ void stsm_x4(uint32_t addr, uint32_t a, uint32_t b, uint32_t c, uint32_t d) {
  asm volatile("stmatrix.sync.aligned.m8n8.x4.shared.b16 [%0], {%1,%2,%3,%4};" :: "r"(addr), "r"(a), "r"(b), "r"(c), "r"(d) : "memory");
}
__device__ __forceinline__ unsigned ld_acquire(const unsigned* p) { unsigned v; asm volatile("ld.acquire.gpu.global.u32 %0, [%1];" : "=r"(v) : "l"(p) : "memory"); return v; }
__device__ __forceinline__ unsigned ld_relaxed(const unsigned* p) { unsigned v; asm volatile("ld.relaxed.gpu.global.u32 %0, [%1];" : "=r"(v) : "l"(p) : "memory"); return v; }
__device__ __forceinline__ void st_release(unsigned* p, unsigned v) { asm volatile("st.release.gpu.global.u32 [%0], %1;" :: "l"(p), "r"(v) : "memory"); }
__device__ __forceinline__ int fresh_ctaid() { int v; asm volatile("mov.u32 %0, %%ctaid.x;" : "=r"(v)); return v; }
__device__ __forceinline__ int fresh_tid() { int v; asm volatile("mov.u32 %0, %%tid.x;" : "=r"(v)); return v; }
__device__ __forceinline__ float ex2(float x) { float y; asm("ex2.approx.ftz.f32 %0, %1;" : "=f"(y) : "f"(x)); return y; }

__device__ __forceinline__ void wgmma_rs_n96_z(float (&d)[48], uint32_t a0, uint32_t a1, uint32_t a2, uint32_t a3, uint32_t db) {
  asm volatile("{\n.reg .pred p;\n.reg .b64 db;\nsetp.ne.b32 p, 0, 0;\nmov.b64 db, {%52, 0x40000040};\n"
    "wgmma.mma_async.sync.aligned.m64n96k16.f32.bf16.bf16 {%0, %1, %2, %3, %4, %5, %6, %7, %8, %9, %10, %11, %12, %13, %14, %15, %16, %17, %18, %19, %20, %21, %22, %23, %24, %25, %26, %27, %28, %29, %30, %31, %32, %33, %34, %35, %36, %37, %38, %39, %40, %41, %42, %43, %44, %45, %46, %47}, {%48, %49, %50, %51}, db, p, 1, 1, 0;\n}\n"
    : "=f"(d[0]), "=f"(d[1]), "=f"(d[2]), "=f"(d[3]), "=f"(d[4]), "=f"(d[5]), "=f"(d[6]), "=f"(d[7]), "=f"(d[8]), "=f"(d[9]), "=f"(d[10]), "=f"(d[11]), "=f"(d[12]), "=f"(d[13]), "=f"(d[14]), "=f"(d[15]), "=f"(d[16]), "=f"(d[17]), "=f"(d[18]), "=f"(d[19]), "=f"(d[20]), "=f"(d[21]), "=f"(d[22]), "=f"(d[23]), "=f"(d[24]), "=f"(d[25]), "=f"(d[26]), "=f"(d[27]), "=f"(d[28]), "=f"(d[29]), "=f"(d[30]), "=f"(d[31]), "=f"(d[32]), "=f"(d[33]), "=f"(d[34]), "=f"(d[35]), "=f"(d[36]), "=f"(d[37]), "=f"(d[38]), "=f"(d[39]), "=f"(d[40]), "=f"(d[41]), "=f"(d[42]), "=f"(d[43]), "=f"(d[44]), "=f"(d[45]), "=f"(d[46]), "=f"(d[47])
    : "r"(a0), "r"(a1), "r"(a2), "r"(a3), "r"(db));
}

__device__ __forceinline__ void wgmma_ss_n48_z(float (&d)[24], uint32_t da, uint32_t db) {
  asm volatile("{\n.reg .pred p;\n.reg .b64 da, db;\nsetp.ne.b32 p, 0, 0;\nmov.b64 da, {%24, 0x40000040};\nmov.b64 db, {%25, 0x40000040};\n"
    "wgmma.mma_async.sync.aligned.m64n48k16.f32.bf16.bf16 {%0, %1, %2, %3, %4, %5, %6, %7, %8, %9, %10, %11, %12, %13, %14, %15, %16, %17, %18, %19, %20, %21, %22, %23}, da, db, p, 1, 1, 0, 0;\n}\n"
    : "=f"(d[0]), "=f"(d[1]), "=f"(d[2]), "=f"(d[3]), "=f"(d[4]), "=f"(d[5]), "=f"(d[6]), "=f"(d[7]), "=f"(d[8]), "=f"(d[9]), "=f"(d[10]), "=f"(d[11]), "=f"(d[12]), "=f"(d[13]), "=f"(d[14]), "=f"(d[15]), "=f"(d[16]), "=f"(d[17]), "=f"(d[18]), "=f"(d[19]), "=f"(d[20]), "=f"(d[21]), "=f"(d[22]), "=f"(d[23])
    : "r"(da), "r"(db));
}

__device__ __forceinline__ void wgmma_ss_n48_ta_z(float (&d)[24], uint32_t da, uint32_t db) {
  asm volatile("{\n.reg .pred p;\n.reg .b64 da, db;\nsetp.ne.b32 p, 0, 0;\nmov.b64 da, {%24, 0x40000040};\nmov.b64 db, {%25, 0x40000040};\n"
    "wgmma.mma_async.sync.aligned.m64n48k16.f32.bf16.bf16 {%0, %1, %2, %3, %4, %5, %6, %7, %8, %9, %10, %11, %12, %13, %14, %15, %16, %17, %18, %19, %20, %21, %22, %23}, da, db, p, 1, 1, 1, 0;\n}\n"
    : "=f"(d[0]), "=f"(d[1]), "=f"(d[2]), "=f"(d[3]), "=f"(d[4]), "=f"(d[5]), "=f"(d[6]), "=f"(d[7]), "=f"(d[8]), "=f"(d[9]), "=f"(d[10]), "=f"(d[11]), "=f"(d[12]), "=f"(d[13]), "=f"(d[14]), "=f"(d[15]), "=f"(d[16]), "=f"(d[17]), "=f"(d[18]), "=f"(d[19]), "=f"(d[20]), "=f"(d[21]), "=f"(d[22]), "=f"(d[23])
    : "r"(da), "r"(db));
}

__device__ __forceinline__ void wgmma_rs_n96(float (&d)[48], uint32_t a0, uint32_t a1, uint32_t a2, uint32_t a3, uint32_t db, int scale_d) {
  asm volatile("{\n.reg .pred p;\n.reg .b64 db;\nsetp.ne.b32 p, %53, 0;\nmov.b64 db, {%52, 0x40000040};\n"
    "wgmma.mma_async.sync.aligned.m64n96k16.f32.bf16.bf16 {%0, %1, %2, %3, %4, %5, %6, %7, %8, %9, %10, %11, %12, %13, %14, %15, %16, %17, %18, %19, %20, %21, %22, %23, %24, %25, %26, %27, %28, %29, %30, %31, %32, %33, %34, %35, %36, %37, %38, %39, %40, %41, %42, %43, %44, %45, %46, %47}, {%48, %49, %50, %51}, db, p, 1, 1, 0;\n}\n"
    : "+f"(d[0]), "+f"(d[1]), "+f"(d[2]), "+f"(d[3]), "+f"(d[4]), "+f"(d[5]), "+f"(d[6]), "+f"(d[7]), "+f"(d[8]), "+f"(d[9]), "+f"(d[10]), "+f"(d[11]), "+f"(d[12]), "+f"(d[13]), "+f"(d[14]), "+f"(d[15]), "+f"(d[16]), "+f"(d[17]), "+f"(d[18]), "+f"(d[19]), "+f"(d[20]), "+f"(d[21]), "+f"(d[22]), "+f"(d[23]), "+f"(d[24]), "+f"(d[25]), "+f"(d[26]), "+f"(d[27]), "+f"(d[28]), "+f"(d[29]), "+f"(d[30]), "+f"(d[31]), "+f"(d[32]), "+f"(d[33]), "+f"(d[34]), "+f"(d[35]), "+f"(d[36]), "+f"(d[37]), "+f"(d[38]), "+f"(d[39]), "+f"(d[40]), "+f"(d[41]), "+f"(d[42]), "+f"(d[43]), "+f"(d[44]), "+f"(d[45]), "+f"(d[46]), "+f"(d[47])
    : "r"(a0), "r"(a1), "r"(a2), "r"(a3), "r"(db), "r"(scale_d));
}

__device__ __forceinline__ void wgmma_ss_n96_ta(float (&d)[48], uint32_t da, uint32_t db, int scale_d) {
  asm volatile("{\n.reg .pred p;\n.reg .b64 da, db;\nsetp.ne.b32 p, %50, 0;\nmov.b64 da, {%48, 0x40000040};\nmov.b64 db, {%49, 0x40000040};\n"
    "wgmma.mma_async.sync.aligned.m64n96k16.f32.bf16.bf16 {%0, %1, %2, %3, %4, %5, %6, %7, %8, %9, %10, %11, %12, %13, %14, %15, %16, %17, %18, %19, %20, %21, %22, %23, %24, %25, %26, %27, %28, %29, %30, %31, %32, %33, %34, %35, %36, %37, %38, %39, %40, %41, %42, %43, %44, %45, %46, %47}, da, db, p, 1, 1, 1, 0;\n}\n"
    : "+f"(d[0]), "+f"(d[1]), "+f"(d[2]), "+f"(d[3]), "+f"(d[4]), "+f"(d[5]), "+f"(d[6]), "+f"(d[7]), "+f"(d[8]), "+f"(d[9]), "+f"(d[10]), "+f"(d[11]), "+f"(d[12]), "+f"(d[13]), "+f"(d[14]), "+f"(d[15]), "+f"(d[16]), "+f"(d[17]), "+f"(d[18]), "+f"(d[19]), "+f"(d[20]), "+f"(d[21]), "+f"(d[22]), "+f"(d[23]), "+f"(d[24]), "+f"(d[25]), "+f"(d[26]), "+f"(d[27]), "+f"(d[28]), "+f"(d[29]), "+f"(d[30]), "+f"(d[31]), "+f"(d[32]), "+f"(d[33]), "+f"(d[34]), "+f"(d[35]), "+f"(d[36]), "+f"(d[37]), "+f"(d[38]), "+f"(d[39]), "+f"(d[40]), "+f"(d[41]), "+f"(d[42]), "+f"(d[43]), "+f"(d[44]), "+f"(d[45]), "+f"(d[46]), "+f"(d[47])
    : "r"(da), "r"(db), "r"(scale_d));
}

__device__ __forceinline__ void wgmma_ss_n48(float (&d)[24], uint32_t da, uint32_t db, int scale_d) {
  asm volatile("{\n.reg .pred p;\n.reg .b64 da, db;\nsetp.ne.b32 p, %26, 0;\nmov.b64 da, {%24, 0x40000040};\nmov.b64 db, {%25, 0x40000040};\n"
    "wgmma.mma_async.sync.aligned.m64n48k16.f32.bf16.bf16 {%0, %1, %2, %3, %4, %5, %6, %7, %8, %9, %10, %11, %12, %13, %14, %15, %16, %17, %18, %19, %20, %21, %22, %23}, da, db, p, 1, 1, 0, 0;\n}\n"
    : "+f"(d[0]), "+f"(d[1]), "+f"(d[2]), "+f"(d[3]), "+f"(d[4]), "+f"(d[5]), "+f"(d[6]), "+f"(d[7]), "+f"(d[8]), "+f"(d[9]), "+f"(d[10]), "+f"(d[11]), "+f"(d[12]), "+f"(d[13]), "+f"(d[14]), "+f"(d[15]), "+f"(d[16]), "+f"(d[17]), "+f"(d[18]), "+f"(d[19]), "+f"(d[20]), "+f"(d[21]), "+f"(d[22]), "+f"(d[23])
    : "r"(da), "r"(db), "r"(scale_d));
}

__device__ __forceinline__ void wgmma_ss_n48_ta(float (&d)[24], uint32_t da, uint32_t db, int scale_d) {
  asm volatile("{\n.reg .pred p;\n.reg .b64 da, db;\nsetp.ne.b32 p, %26, 0;\nmov.b64 da, {%24, 0x40000040};\nmov.b64 db, {%25, 0x40000040};\n"
    "wgmma.mma_async.sync.aligned.m64n48k16.f32.bf16.bf16 {%0, %1, %2, %3, %4, %5, %6, %7, %8, %9, %10, %11, %12, %13, %14, %15, %16, %17, %18, %19, %20, %21, %22, %23}, da, db, p, 1, 1, 1, 0;\n}\n"
    : "+f"(d[0]), "+f"(d[1]), "+f"(d[2]), "+f"(d[3]), "+f"(d[4]), "+f"(d[5]), "+f"(d[6]), "+f"(d[7]), "+f"(d[8]), "+f"(d[9]), "+f"(d[10]), "+f"(d[11]), "+f"(d[12]), "+f"(d[13]), "+f"(d[14]), "+f"(d[15]), "+f"(d[16]), "+f"(d[17]), "+f"(d[18]), "+f"(d[19]), "+f"(d[20]), "+f"(d[21]), "+f"(d[22]), "+f"(d[23])
    : "r"(da), "r"(db), "r"(scale_d));
}

__device__ __forceinline__ void wgmma_ss_n192_ta(float (&d)[48], float (&e)[48], uint32_t da, uint32_t db, int scale_d) {
  asm volatile("{\n.reg .pred p;\n.reg .b64 da, db;\nsetp.ne.b32 p, %98, 0;\nmov.b64 da, {%96, 0x40000040};\nmov.b64 db, {%97, 0x40000040};\n"
    "wgmma.mma_async.sync.aligned.m64n192k16.f32.bf16.bf16 {%0, %1, %2, %3, %4, %5, %6, %7, %8, %9, %10, %11, %12, %13, %14, %15, %16, %17, %18, %19, %20, %21, %22, %23, %24, %25, %26, %27, %28, %29, %30, %31, %32, %33, %34, %35, %36, %37, %38, %39, %40, %41, %42, %43, %44, %45, %46, %47, %48, %49, %50, %51, %52, %53, %54, %55, %56, %57, %58, %59, %60, %61, %62, %63, %64, %65, %66, %67, %68, %69, %70, %71, %72, %73, %74, %75, %76, %77, %78, %79, %80, %81, %82, %83, %84, %85, %86, %87, %88, %89, %90, %91, %92, %93, %94, %95}, da, db, p, 1, 1, 1, 0;\n}\n"
    : "+f"(d[0]), "+f"(d[1]), "+f"(d[2]), "+f"(d[3]), "+f"(d[4]), "+f"(d[5]), "+f"(d[6]), "+f"(d[7]), "+f"(d[8]), "+f"(d[9]), "+f"(d[10]), "+f"(d[11]), "+f"(d[12]), "+f"(d[13]), "+f"(d[14]), "+f"(d[15]), "+f"(d[16]), "+f"(d[17]), "+f"(d[18]), "+f"(d[19]), "+f"(d[20]), "+f"(d[21]), "+f"(d[22]), "+f"(d[23]), "+f"(d[24]), "+f"(d[25]), "+f"(d[26]), "+f"(d[27]), "+f"(d[28]), "+f"(d[29]), "+f"(d[30]), "+f"(d[31]), "+f"(d[32]), "+f"(d[33]), "+f"(d[34]), "+f"(d[35]), "+f"(d[36]), "+f"(d[37]), "+f"(d[38]), "+f"(d[39]), "+f"(d[40]), "+f"(d[41]), "+f"(d[42]), "+f"(d[43]), "+f"(d[44]), "+f"(d[45]), "+f"(d[46]), "+f"(d[47]), "+f"(e[0]), "+f"(e[1]), "+f"(e[2]), "+f"(e[3]), "+f"(e[4]), "+f"(e[5]), "+f"(e[6]), "+f"(e[7]), "+f"(e[8]), "+f"(e[9]), "+f"(e[10]), "+f"(e[11]), "+f"(e[12]), "+f"(e[13]), "+f"(e[14]), "+f"(e[15]), "+f"(e[16]), "+f"(e[17]), "+f"(e[18]), "+f"(e[19]), "+f"(e[20]), "+f"(e[21]), "+f"(e[22]), "+f"(e[23]), "+f"(e[24]), "+f"(e[25]), "+f"(e[26]), "+f"(e[27]), "+f"(e[28]), "+f"(e[29]), "+f"(e[30]), "+f"(e[31]), "+f"(e[32]), "+f"(e[33]), "+f"(e[34]), "+f"(e[35]), "+f"(e[36]), "+f"(e[37]), "+f"(e[38]), "+f"(e[39]), "+f"(e[40]), "+f"(e[41]), "+f"(e[42]), "+f"(e[43]), "+f"(e[44]), "+f"(e[45]), "+f"(e[46]), "+f"(e[47])
    : "r"(da), "r"(db), "r"(scale_d));
}


template <int NT = 12>
__device__ __forceinline__ void store_acc_T(const float* acc, uint32_t tile_addr_plus_fragoff) {
#pragma unroll
  for (int jj = 0; jj < NT; jj += 2) {
    stsm_x4_t(tile_addr_plus_fragoff + jj * 1024,
              pack_bf16(acc[4 * jj + 0], acc[4 * jj + 1]), pack_bf16(acc[4 * jj + 2], acc[4 * jj + 3]),
              pack_bf16(acc[4 * jj + 4], acc[4 * jj + 5]), pack_bf16(acc[4 * jj + 6], acc[4 * jj + 7]));
  }
}

template <bool FIRST>
__device__ __forceinline__ void qproj_tile(int j, uint32_t sb, int g, int lane, uint32_t frag_off, uint32_t (&wr)[NWQ][4],
                                           int& slot, uint32_t& xph, uint32_t& early) {
  float acc[48];
  const uint32_t bars = sb + OFF_BAR;
  const uint32_t xlo = opaque(desc_lo(sb + OFF_X, 16));
  int prev = 0;
  mbar_wait(bars + (B_XFULL + slot) * 8, xph);
  if (!FIRST) named_bar(4 + g, 256);
#pragma unroll
  for (int ks = 0; ks < 8; ++ks) {
    if (FIRST) {
      mbar_wait(bars + (B_WFULL + g * 8 + ks) * 8, 0);
#pragma unroll
      for (int kk = 0; kk < 4; ++kk)
        if (ks * 4 + kk < NWQ) ldsm_x4_t(wr[ks * 4 + kk], sb + (g ? w_stage(1, ks) : w_stage(0, ks)) + kk * 2048 + frag_off);
      if (ks == 2) { __syncwarp(); if (lane == 0) mbar_arrive(bars + (B_WDONE + 1) * 8); }
      if (ks == 7) {
        __syncwarp();
        if (lane == 0) mbar_arrive(bars + B_WDONE * 8);
        if (g == 1 && lane < 2) mbar_arrive_cta(bars + B_WFREE * 8, lane);
      }
    }
    const uint32_t xs = xlo + slot * (X_SLOT >> 4);
    wg_fence();
#pragma unroll
    for (int kk = 0; kk < 4; ++kk) {
      if (ks == 0 && kk == 0)
        wgmma_rs_n96_z(acc, wr[0][0], wr[0][1], wr[0][2], wr[0][3], xs);
      else if (ks * 4 + kk < NWQ)
        wgmma_rs_n96(acc, wr[ks * 4 + kk][0], wr[ks * 4 + kk][1], wr[ks * 4 + kk][2], wr[ks * 4 + kk][3], xs + kk * 2, 1);
      else
        wgmma_ss_n96_ta(acc, xlo + ((OFF_WP - OFF_X + (kk - 2) * 2048) >> 4) + g * 256, xs + kk * 2, 1);
    }
    wg_commit();
    if (ks == PP_HAND && !(FIRST && g == 0) && !(j == 7 && g == 1)) named_arrive(4 + (g ^ 1), 256);
    const int cur = slot;
    if (++slot == X_NS) { slot = 0; xph ^= 1; }
    if (ks < 7) mbar_wait(bars + (B_XFULL + slot) * 8, xph);
    if (ks == 6 && !FIRST) {
      early = mbar_test(bars + (B_QEMPTY + (j & 1)) * 8, ((j >> 1) - 1) & 1) | (mbar_test(bars + B_VFULL * 8, (j - 1) & 1) << 1) | (mbar_test(bars + B_PFULL * 8, (j - 1) & 1) << 2);
    }
    if (ks > 0) {
      wg_wait<1>();
      if (lane < 2) mbar_arrive_cta(bars + (B_XEMPTY + prev) * 8, lane);
    }
    prev = cur;
  }
  wg_wait<0>();
  if (lane < 2) mbar_arrive_cta(bars + (B_XEMPTY + prev) * 8, lane);
  const int buf = j & 1;
  if (FIRST) mbar_wait(bars + B_WDONE * 8, 0);
  if (j >= 2 && !(early & 1)) mbar_wait(bars + (B_QEMPTY + buf) * 8, ((j >> 1) - 1) & 1);
  store_acc_T<12>(acc, sb + OFF_QO + buf * QO_BUF + g * 12288 + frag_off);
  fence_async_smem();
  __syncwarp();
  if (lane == 0) mbar_arrive(bars + (B_QFULL + buf) * 8);
}

__device__ __forceinline__ void pv_tile(int j, uint32_t sb, int g, int lane, uint32_t frag_off, uint32_t early) {
  float o0[24], o1[24];
  const uint32_t bars = sb + OFF_BAR;
  const uint32_t vlo = desc_lo(sb + OFF_V + g * 6144, 16), plo = desc_lo(sb + OFF_P, 16);
  if (!(early & 2)) mbar_wait(bars + B_VFULL * 8, j & 1);
  if (!(early & 4)) mbar_wait(bars + B_PFULL * 8, j & 1);
  wg_fence();
#pragma unroll
  for (int kk = 0; kk < 3; ++kk) {
    if (kk == 0) {
      wgmma_ss_n48_ta_z(o0, vlo, plo);
      wgmma_ss_n48_ta_z(o1, vlo + 768, plo + 384);
    } else {
      wgmma_ss_n48_ta(o0, vlo + kk * 128, plo + kk * 2, 1);
      wgmma_ss_n48_ta(o1, vlo + 768 + kk * 128, plo + 384 + kk * 2, 1);
    }
  }
  wg_commit();
  wg_wait<0>();
  if (lane == 0) mbar_arrive(bars + B_VEMPTY * 8);
  const int buf = j & 1;
  store_acc_T<6>(o0, sb + OFF_QO + buf * QO_BUF + g * 12288 + frag_off);
  store_acc_T<6>(o1, sb + OFF_QO + buf * QO_BUF + g * 12288 + frag_off + 6144);
  fence_async_smem();
  __syncwarp();
  if (lane == 0) mbar_arrive(bars + (B_OFULL + buf) * 8);
}

__device__ __forceinline__ void softmax_exp(float (&s)[24], float& i0, float& i1) {
  const float sc = 0.08838834764831845f * 1.4426950408889634f;
  float m0 = fmaxf(s[0], s[1]), m1 = fmaxf(s[2], s[3]);
#pragma unroll
  for (int i = 1; i < 6; ++i) { m0 = fmaxf(m0, fmaxf(s[4 * i], s[4 * i + 1])); m1 = fmaxf(m1, fmaxf(s[4 * i + 2], s[4 * i + 3])); }
  m0 = fmaxf(m0, __shfl_xor_sync(0xffffffffu, m0, 1)); m1 = fmaxf(m1, __shfl_xor_sync(0xffffffffu, m1, 1));
  m0 = fmaxf(m0, __shfl_xor_sync(0xffffffffu, m0, 2)); m1 = fmaxf(m1, __shfl_xor_sync(0xffffffffu, m1, 2));
  const float b0 = -m0 * sc, b1 = -m1 * sc;
  float l0 = 0.f, l1 = 0.f;
#pragma unroll
  for (int i = 0; i < 6; ++i) {
    s[4 * i] = ex2(fmaf(s[4 * i], sc, b0)); s[4 * i + 1] = ex2(fmaf(s[4 * i + 1], sc, b0));
    s[4 * i + 2] = ex2(fmaf(s[4 * i + 2], sc, b1)); s[4 * i + 3] = ex2(fmaf(s[4 * i + 3], sc, b1));
    l0 += s[4 * i] + s[4 * i + 1]; l1 += s[4 * i + 2] + s[4 * i + 3];
  }
  l0 += __shfl_xor_sync(0xffffffffu, l0, 1); l1 += __shfl_xor_sync(0xffffffffu, l1, 1);
  l0 += __shfl_xor_sync(0xffffffffu, l0, 2); l1 += __shfl_xor_sync(0xffffffffu, l1, 2);
  i0 = __fdividef(1.f, l0); i1 = __fdividef(1.f, l1);
}


__device__ __forceinline__ void issue_scores(float (&s)[24], uint32_t qlo, uint32_t klo) {
#pragma unroll
  for (int kk = 0; kk < 8; ++kk) {
    if (kk == 0) wgmma_ss_n48_z(s, qlo, klo);
    else wgmma_ss_n48(s, qlo + (kk >> 2) * 768 + (kk & 3) * 2, klo + (kk >> 2) * 384 + (kk & 3) * 2, 1);
  }
}
__device__ __forceinline__ void store_p(const float (&s)[24], float i0, float i1, uint32_t a, int lane) {
#pragma unroll
  for (int jj = 0; jj < 6; jj += 2) {
    const int oct = jj + (lane >> 4);
    stsm_x4(a + ((oct ^ (lane & 7)) << 4), pack_bf16(s[4 * jj] * i0, s[4 * jj + 1] * i0), pack_bf16(s[4 * jj + 2] * i1, s[4 * jj + 3] * i1),
            pack_bf16(s[4 * jj + 4] * i0, s[4 * jj + 5] * i0), pack_bf16(s[4 * jj + 6] * i1, s[4 * jj + 7] * i1));
  }
}

__device__ __forceinline__ void load_w(uint32_t sb, const CUtensorMap* m, int head, int ks) {
  const uint64_t pol = policy_evict_first();
#pragma unroll
  for (int g = 0; g < 2; ++g) {
    const uint32_t wb = sb + OFF_BAR + (B_WFULL + g * 8 + ks) * 8;
    const uint32_t d = sb + (ks < 3 ? OFF_K + (ks * 2 + g) * 8192 : (ks < 6 ? OFF_QO + ((ks - 3) * 2 + g) * 8192 : (g ? 98304 : OFF_P) + (ks - 6) * 8192));
    mbar_expect_tx(wb, 8192);
    tma_ld_hint(d, m, head * 128 + g * 64, ks * 64, wb, pol);
    tma_ld_hint(ks == 7 ? sb + OFF_WP + g * 4096 : d + 4096, m, head * 128 + g * 64, ks * 64 + 32, wb, pol);
  }
}

__global__ void __cluster_dims__(2, 1, 1) __launch_bounds__(NTHREADS, 1)
fused_kernel(const __grid_constant__ Params P) {
  extern __shared__ uint8_t smem_raw[];
  const uint32_t sb = (smem_u32(smem_raw) + 1023u) & ~1023u;
  const uint32_t bars = sb + OFF_BAR;
  const int tid = threadIdx.x, warp = tid >> 5, lane = tid & 31;
  const int rank = blockIdx.x & 1;
  const int cid = blockIdx.x >> 1;
  const int br = cid >> 5;
  const int c5 = cid & 31;
  const int pj = c5 >> 1, half = c5 & 1;
  const int head = pj * 2 + rank;
  const int r0 = pj & 3;
  const int T = c5 >> 2, kh = (c5 >> 1) & 1, cs = (c5 & 1) * 2 + rank;

  if (tid == 384) {
    asm volatile("prefetch.tensormap [%0];" :: "l"(&P.wq[br]) : "memory");
    for (int i = 0; i < 16; ++i) mbar_init(bars + (B_WFULL + i) * 8, 1);
    asm volatile("fence.mbarrier_init.release.cluster;" ::: "memory");
    fence_async_smem();
  } else if (tid == 0) {
    for (int i = 0; i < X_NS; ++i) { mbar_init(bars + (B_XFULL + i) * 8, 1); mbar_init(bars + (B_XEMPTY + i) * 8, 16); }
    for (int i = 0; i < 2; ++i) { mbar_init(bars + (B_QFULL + i) * 8, 8); mbar_init(bars + (B_QEMPTY + i) * 8, 1); }
    for (int i = 0; i < 2; ++i) { mbar_init(bars + (B_KFULL + i) * 8, 1); mbar_init(bars + (B_VFULL + i) * 8, 1); mbar_init(bars + (B_WDONE + i) * 8, 8); }
    asm volatile("fence.mbarrier_init.release.cluster;" ::: "memory");
  } else if (tid == 32) {
    for (int i = 0; i < P2_NST; ++i) { mbar_init(bars + (B_P2FULL + i) * 8, 1); mbar_init(bars + (B_P2EMPTY + i) * 8, 16); }
    mbar_init(bars + B_KEMPTY * 8, 4);
    mbar_init(bars + B_WFREE * 8, 8);
    mbar_init(bars + B_VEMPTY * 8, 8);
    mbar_init(bars + B_PFULL * 8, 3);
    for (int i = 0; i < 2; ++i) { mbar_init(bars + (B_OFULL + i) * 8, 8); mbar_init(bars + (B_OST + i) * 8, 2); }
    asm volatile("fence.mbarrier_init.release.cluster;" ::: "memory");
  } else if (tid == 64) {
    for (int i = 0; i < 20; ++i) mbar_init(bars + (B_HREADY + i) * 8, 1);
    mbar_init(bars + B_KDONE * 8, 4);
    asm volatile("fence.mbarrier_init.release.cluster;" ::: "memory");
  } else if (tid == 96) {
    l2_prefetch((const char*)P.xp[br] + (size_t)(blockIdx.x & 63) * 24576, 24576);
    asm volatile("prefetch.tensormap [%0];" :: "l"(&P.x[br]) : "memory");
    asm volatile("prefetch.tensormap [%0];" :: "l"(&P.k[br]) : "memory");
    asm volatile("prefetch.tensormap [%0];" :: "l"(&P.v[br]) : "memory");
    asm volatile("prefetch.tensormap [%0];" :: "l"(&P.o) : "memory");
  }
  __syncwarp();
  asm volatile("barrier.cluster.arrive.relaxed.aligned;" ::: "memory");
  if (tid == 384) {
    load_w(sb, &P.wq[br], head, 0);
  }
  __syncwarp();
  asm volatile("barrier.cluster.wait.aligned;" ::: "memory");

  if (warp < 8) {
    asm volatile("setmaxnreg.inc.sync.aligned.u32 200;");
    const int g = warp >> 2;
    const uint32_t frag_off = ((lane >> 4) * 8 + (lane & 7)) * 128 + (((2 * (warp & 3) + ((lane >> 3) & 1)) ^ (lane & 7)) << 4);
    {
      uint32_t wr[NWQ][4];
      int slot = 0; uint32_t xph = 0, early = 0;
      qproj_tile<true>(0, sb, g, lane, frag_off, wr, slot, xph, early);
#pragma unroll 1
      for (int j = 1; j < 8; ++j) {
        qproj_tile<false>(j, sb, g, lane, frag_off, wr, slot, xph, early);
        pv_tile(j - 1, sb, g, lane, frag_off, early);
      }
    }
    {
      const int bid = fresh_ctaid(), tid = fresh_tid();
      const int br = bid >> 6, T = (bid >> 3) & 7, kh = (bid >> 2) & 1, cs = bid & 3;
      float accK[48], accS[48];
#pragma unroll
      for (int i = 0; i < 48; ++i) { accK[i] = 0.f; accS[i] = 0.f; }
      const uint32_t tag = (ld_relaxed(&g_done) / NCTA + 1u) & 3u;
      int st = 0; uint32_t ph = 0; int prev = 0;
      uint32_t alo = desc_lo(sb + p2_a(0, g), 16), blo = desc_lo(sb + p2_b(0), 16);
      mbar_wait(bars + B_P2FULL * 8, 0);
#pragma unroll 1
      for (int it = 0; it < P2_FULL; ++it) {
        wg_fence();
#pragma unroll
        for (int kk = 0; kk < 4; ++kk) wgmma_ss_n192_ta(accK, accS, alo + kk * 128, blo + kk * 2, 1);
        wg_commit();
        const int cur = st;
        if (++st == P2_NST) { st = 0; ph ^= 1; }
        alo = opaque(desc_lo(sb + p2_a(st, g), 16)); blo = opaque(desc_lo(sb + p2_b(st), 16));
        if (it == PV7_AT) {
          wg_wait<0>();
          if (lane < 2) { if (it > 0) mbar_arrive_cta(bars + (B_P2EMPTY + prev) * 8, lane); }
          pv_tile(7, sb, g, lane, frag_off, 0);
          mbar_wait(bars + (B_P2FULL + st) * 8, ph);
        } else {
          mbar_wait(bars + (B_P2FULL + st) * 8, ph);
          if (it > 0) {
            wg_wait<1>();
            if (lane < 2) mbar_arrive_cta(bars + (B_P2EMPTY + prev) * 8, lane);
          }
        }
        prev = cur;
      }
      wg_wait<0>();
      if (lane < 2) mbar_arrive_cta(bars + (B_P2EMPTY + prev) * 8, lane);
      uint4* dst = g_part + (size_t)bid * 12 * 256 + tid;
#pragma unroll
      for (int it = P2_FULL; it < P2_ITS; ++it) {
        wg_fence();
#pragma unroll
        for (int kk = 0; kk < 4; ++kk) wgmma_ss_n96_ta(accK, alo + kk * 128, blo + kk * 2, 1);
        wg_commit();
        const int cur = st;
        if (++st == P2_NST) { st = 0; ph ^= 1; }
        alo = opaque(desc_lo(sb + p2_a(st, g), 16)); blo = opaque(desc_lo(sb + p2_b(st), 16));
        if (it == P2_FULL) {
#pragma unroll
          for (int i = 0; i < 12; ++i)
            asm volatile("st.global.v4.b32 [%0], {%1, %2, %3, %4};" :: "l"(dst + i * 256), "r"((__float_as_uint(accS[4 * i]) & ~3u) | tag),
                         "r"((__float_as_uint(accS[4 * i + 1]) & ~3u) | tag), "r"((__float_as_uint(accS[4 * i + 2]) & ~3u) | tag),
                         "r"((__float_as_uint(accS[4 * i + 3]) & ~3u) | tag) : "memory");
        }
        if (it < P2_ITS - 1) mbar_wait(bars + (B_P2FULL + st) * 8, ph);
        if (it > P2_FULL) {
          wg_wait<1>();
          if (it <= P2_ITS - 5 && lane < 2) mbar_arrive_cta(bars + (B_P2EMPTY + prev) * 8, lane);
        }
        prev = cur;
      }
      const uint4* src = g_part + (size_t)(bid ^ 4) * 12 * 256 + tid;
      {
        uint4 v[12];
        uint32_t spins = 0;
        bool ok;
        do {
#pragma unroll
          for (int i = 0; i < 12; ++i) {
            asm volatile("ld.relaxed.gpu.global.v4.b32 {%0, %1, %2, %3}, [%4];" : "=r"(v[i].x), "=r"(v[i].y), "=r"(v[i].z), "=r"(v[i].w) : "l"(src + i * 256) : "memory");
          }
          uint32_t bad = 0;
#pragma unroll
          for (int i = 0; i < 12; ++i) bad |= (v[i].x ^ tag) | (v[i].y ^ tag) | (v[i].z ^ tag) | (v[i].w ^ tag);
          ok = (bad & 3u) == 0;
          if (!ok) __nanosleep(100);
          if (++spins > (1u << 22)) __trap();
        } while (!ok);
        wg_wait<0>();
#pragma unroll
        for (int i = 0; i < 12; ++i) {
          accK[4 * i] += __uint_as_float(v[i].x & ~3u); accK[4 * i + 1] += __uint_as_float(v[i].y & ~3u);
          accK[4 * i + 2] += __uint_as_float(v[i].z & ~3u); accK[4 * i + 3] += __uint_as_float(v[i].w & ~3u);
        }
      }
      named_bar(1, 256);
      store_acc_T(accK, sb + g * 12288 + frag_off);
      fence_async_smem();
      named_bar(2 + g, 128);
      if ((tid & 127) == 0) {
        tma_st(&P.out_st, br * 512 + cs * 128 + g * 64, T * 192 + kh * 96, sb + g * 12288);
        bulk_commit();
        bulk_wait_read<0>();
        if (tid == 0) atomicAdd(&g_done, 1u);
      }
    }
  } else if (warp < 12) {
    asm volatile("setmaxnreg.dec.sync.aligned.u32 88;");
    const int w = warp - 8;
    const uint32_t pa = sb + OFF_P + (16 * w + ((lane >> 3) & 1) * 8 + (lane & 7)) * 128;
    const uint32_t klo = desc_lo(sb + OFF_K, 16);
#pragma unroll 1
    for (int j = 0; j < 8; ++j) {
      const int buf = j & 1;
      const uint32_t qlo = desc_lo(sb + OFF_QO + buf * QO_BUF, 16);
      float sa[24], sb2[24], i0, i1;
      mbar_wait(bars + (B_QFULL + buf) * 8, (j >> 1) & 1);
      mbar_wait(bars + (B_KFULL + 0) * 8, j & 1);
      wg_fence();
      issue_scores(sa, qlo, klo);
      issue_scores(sb2, qlo + 384, klo + 768);
      wg_commit();
      wg_wait<0>();
      if (lane == 0) mbar_arrive(bars + (j == 7 ? B_KDONE : B_KEMPTY) * 8);
      float i2, i3;
      softmax_exp(sa, i0, i1);
      softmax_exp(sb2, i2, i3);
      if (j > 0) mbar_wait(bars + B_VEMPTY * 8, (j - 1) & 1);
      if (w < 3) {
        store_p(sa, i0, i1, pa, lane);
        store_p(sb2, i2, i3, pa + 6144, lane);
        fence_async_smem();
        __syncwarp();
        if (lane == 0) mbar_arrive(bars + B_PFULL * 8);
      }
    }
  } else {
    asm volatile("setmaxnreg.dec.sync.aligned.u32 24;");
    auto tile_of = [&](int j) { return half * 8 + ((((r0 + (j >> 1)) & 3) << 1) | (j & 1)); };
    if (tid == 416) {
      const uint64_t pol = policy_evict_first();
      mbar_wait(bars + (B_WDONE + 1) * 8, 0);
      int kj = 0, vj = 0;
      uint32_t spins = 0;
      while (kj < 8 || vj < 8) {
        if (kj < 8 && (kj == 0 || mbar_test(bars + B_KEMPTY * 8, (kj - 1) & 1))) {
          for (int sub = 0; sub < 2; ++sub) {
            const int row = ((tile_of(kj) * 2 + sub) * 32 + head) * 48;
            const uint32_t kbar = bars + B_KFULL * 8, kd = sb + OFF_K + sub * 12288;
            if (sub == 0) mbar_expect_tx(kbar, 24576);
            tma_ld_hint(kd, &P.k[br], 0, row, kbar, pol);
            tma_ld_hint(kd + 6144, &P.k[br], 64, row, kbar, pol);
          }
          ++kj;
        }
        if (vj < 8 && (vj == 0 || mbar_test(bars + B_VEMPTY * 8, (vj - 1) & 1))) {
          for (int sub = 0; sub < 2; ++sub) {
            const int row = ((tile_of(vj) * 2 + sub) * 32 + head) * 48;
            const uint32_t vbar = bars + B_VFULL * 8, vd = sb + OFF_V + sub * 12288;
            if (sub == 0) mbar_expect_tx(vbar, 24576);
            tma_ld_hint(vd, &P.v[br], 0, row, vbar, pol);
            tma_ld_hint(vd + 6144, &P.v[br], 64, row, vbar, pol);
          }
          ++vj;
        }
        __nanosleep(20);
        if (++spins > (1u << 24)) __trap();
      }
    } else if (tid == 448) {
      const unsigned epoch = ld_relaxed(&g_done) / NCTA + 1u;
      for (int j = 0; j < 8; ++j) {
        const int buf = j & 1;
        mbar_wait(bars + (B_OFULL + buf) * 8, (j >> 1) & 1);
        const int t = tile_of(j);
        const uint32_t qb = sb + OFF_QO + buf * QO_BUF;
        tma_st(&P.o, head * 128, br * 1536 + t * 96, qb);
        tma_st(&P.o, head * 128 + 64, br * 1536 + t * 96, qb + 12288);
        bulk_commit();
        bulk_wait_read<0>();
        mbar_arrive(bars + (B_QEMPTY + buf) * 8);
        if (j >= 6) { mbar_arrive_cta(bars + (B_OST + j - 6) * 8, 0); mbar_arrive_cta(bars + (B_OST + j - 6) * 8, 1); }
        bulk_wait<0>();
        asm volatile("fence.proxy.async.global;" ::: "memory");
        st_release(&g_oflag[(br * 16 + t) * 32 + head], epoch);
      }
    } else if (warp == 15) {
      const unsigned epoch = ld_relaxed(&g_done) / NCTA + 1u;
      const int idx = lane < 16 ? lane : 14 + (lane & 1);
      const int khl = lane < 16 ? kh : (kh ^ ((lane >> 1) & 1));
      const int q = (idx >> 2) & 3, hi = idx & 3;
      const int h2 = (khl * 8 + (hi >> 1) * 4 + k_order(q, T & 3)) * 2 + (hi & 1);
      const unsigned* fp = &g_oflag[(br * 16 + T * 2 + (lane < 16 ? rank : kh)) * 32 + h2];
      bool done = lane >= 20;
      uint32_t it = 0;
      while (!__all_sync(0xffffffffu, done)) {
        if (!done && ld_acquire(fp) == epoch) { mbar_arrive(bars + (B_HREADY + lane) * 8); done = true; }
        __nanosleep(700);
        if (++it > (1u << 22)) __trap();
      }
    } else if (tid == 384) {
      int slot = 0; uint32_t ph = 1;
      for (int j = 0; j < 8; ++j) {
        const int xrow = tile_of(j) * 96;
        for (int ks = 0; ks < 8; ++ks) {
          if (j == 1 && ks == 0) mbar_wait(bars + B_WFREE * 8, 0);
          mbar_wait(bars + (B_XEMPTY + slot) * 8, ph);
          const uint32_t xb = bars + (B_XFULL + slot) * 8;
          mbar_expect_tx(xb, X_SLOT);
          if ((ks & 1) == rank) tma_ld_mc(sb + OFF_X + slot * X_SLOT, &P.x[br], ks * 64, xrow, xb);
          if (++slot == X_NS) { slot = 0; ph ^= 1; }
          if (j == 0 && ks < 7) load_w(sb, &P.wq[br], head, ks + 1);
        }
        if (j == 6) {
          asm volatile("prefetch.tensormap [%0];" :: "l"(&P.wo[br]) : "memory");
          asm volatile("prefetch.tensormap [%0];" :: "l"(&P.out_st) : "memory");
        }
      }
      const int Tq = T & 3;
      const uint64_t pol2 = policy_evict_first();
      const int orow = br * 1536 + T * 192 + rank * 96;
      const uint32_t odst = (rank == kh) ? 0 : 12288;
      const uint32_t xph = ph;
      int st = 0; ph = 0;
      for (int it = 0; it < P2_ITS; ++it) {
        const bool tail = it >= P2_FULL;
        const int sl = tail ? P2_FULL + ((it - P2_FULL) >> 1) : it;
        const int khl = tail ? (kh ^ (it & 1)) : kh;
        const int q = sl >> 3, hi = (sl >> 1) & 3;
        const int h2 = (khl * 8 + (hi >> 1) * 4 + k_order(q, Tq)) * 2 + (hi & 1);
        const int k0 = h2 * 128 + (sl & 1) * 64;
        if (it < P2_NST) {
          if (it == 0) { for (int i = 1; i < 5; ++i) mbar_wait(bars + (B_XEMPTY + i) * 8, xph); }
          else if (it == 1) { for (int i = 5; i < 8; ++i) mbar_wait(bars + (B_XEMPTY + i) * 8, xph); }
          else if (it == 2) { mbar_wait(bars + B_KDONE * 8, 0); mbar_wait(bars + B_OST * 8, 0); }
          else if (it == 3) { mbar_wait(bars + (B_XEMPTY + 8) * 8, xph); mbar_wait(bars + B_XEMPTY * 8, xph ^ 1); }
          else mbar_wait(bars + (B_OST + 1) * 8, 0);
        } else {
          mbar_wait(bars + (B_P2EMPTY + st) * 8, ph ^ 1);
        }
        const uint32_t fb = bars + (B_P2FULL + st) * 8;
        mbar_expect_tx(fb, tail ? 28672 : 40960);
        tma_ld(sb + p2_a(st, 0), &P.wo[br], cs * 128, k0, fb);
        tma_ld(sb + p2_a(st, 1), &P.wo[br], cs * 128 + 64, k0, fb);
        if (!tail) {
          if ((it & 1) == 0) { mbar_wait(bars + (B_HREADY + (it >> 1)) * 8, 0); asm volatile("fence.proxy.async.global;" ::: "memory"); }
          tma_ld_mc_hint(sb + p2_b(st) + odst, &P.o, k0, orow, fb, pol2);
        } else if ((it & 1) == rank) {
          mbar_wait(bars + (B_HREADY + 16 + (it & 1) * 2 + ((sl >> 1) & 1)) * 8, 0);
          asm volatile("fence.proxy.async.global;" ::: "memory");
          tma_ld_mc_hint(sb + p2_b(st), &P.o, k0, br * 1536 + T * 192 + kh * 96, fb, pol2);
        }
        if (++st == P2_NST) { st = 0; ph ^= 1; }
      }
    }
  }
}

typedef CUresult (*EncodeFn)(CUtensorMap*, CUtensorMapDataType, cuuint32_t, void*, const cuuint64_t*, const cuuint64_t*,
                             const cuuint32_t*, const cuuint32_t*, CUtensorMapInterleave, CUtensorMapSwizzle,
                             CUtensorMapL2promotion, CUtensorMapFloatOOBfill);

static void make_map(EncodeFn enc, CUtensorMap* m, const void* ptr, uint64_t cols, uint64_t rows, uint32_t box_rows) {
  cuuint64_t gdim[2] = {cols, rows};
  cuuint64_t gstr[1] = {cols * 2};
  cuuint32_t box[2] = {64, box_rows};
  cuuint32_t es[2] = {1, 1};
  enc(m, CU_TENSOR_MAP_DATA_TYPE_BFLOAT16, 2, const_cast<void*>(ptr), gdim, gstr, box, es, CU_TENSOR_MAP_INTERLEAVE_NONE,
      CU_TENSOR_MAP_SWIZZLE_128B, CU_TENSOR_MAP_L2_PROMOTION_L2_128B, CU_TENSOR_MAP_FLOAT_OOB_FILL_NONE);
}

}

extern "C" void kernel_launch(void* const* d_in, const int* in_sizes, int n_in, void* d_out, int out_size) {
  using namespace fk;
  (void)in_sizes; (void)n_in; (void)out_size;
  static EncodeFn enc = nullptr;
  static void* o_ptr = nullptr;
  if (!enc) {
    cudaDriverEntryPointQueryResult qr;
    cudaGetDriverEntryPoint("cuTensorMapEncodeTiled", (void**)&enc, cudaEnableDefault, &qr);
    cudaGetSymbolAddress(&o_ptr, g_O);
    cudaFuncSetAttribute(fused_kernel, cudaFuncAttributeMaxDynamicSharedMemorySize, SMEM_BYTES);
  }
  Params P;
  for (int b = 0; b < 2; ++b) {
    make_map(enc, &P.x[b], d_in[5 * b + 0], 512, 1536, 96);
    make_map(enc, &P.k[b], d_in[5 * b + 1], 128, 32 * 32 * 48, 48);
    make_map(enc, &P.v[b], d_in[5 * b + 2], 128, 32 * 32 * 48, 48);
    make_map(enc, &P.wq[b], d_in[5 * b + 3], 4096, 512, 32);
    make_map(enc, &P.wo[b], d_in[5 * b + 4], 512, 4096, 64);
    P.xp[b] = (const __nv_bfloat16*)d_in[5 * b + 0];
  }
  make_map(enc, &P.o, o_ptr, 4096, 3072, 96);
  make_map(enc, &P.out_st, d_out, 1024, 1536, 96);
  fused_kernel<<<NCTA, NTHREADS, SMEM_BYTES, cudaStreamPerThread>>>(P);
}
```
